```python
import torch

def _softmax(x, axis=-1):
    return torch.softmax(x, dim=axis)

def _gelu(x):
    return torch.nn.functional.gelu(x, approximate='tanh')

def _silu(x):
    return torch.nn.functional.silu(x)

def _sigmoid(x):
    return torch.sigmoid(x)

def _layernorm(x, axis=-1, eps=1e-05):
    m = x.mean(dim=axis, keepdim=True)
    v = x.var(dim=axis, keepdim=True, unbiased=False)
    return (x - m) / torch.sqrt(v + eps)

def _scatter_add(tgt, idx, src, axis=0):
    return tgt.clone().index_add_(axis, idx, src)

def _segment_sum(src, seg, n):
    out = torch.zeros((n,) + src.shape[1:], dtype=src.dtype)
    return out.index_add_(0, seg, src)

def _pad(x, pw):
    flat = tuple((v for pair in reversed(pw) for v in pair))
    return torch.nn.functional.pad(x, flat)
kernel_name = 'adaLN_cond__gqa_block_cached__glu_gated_swiglu__decode'

def setup_inputs():

    _w = lambda a: (lambda t: t.to(torch.bfloat16) if t.is_floating_point() else t)(torch.as_tensor(a))

    def _A_setup():
        B, Sq, D = (1, 1, 640)
        Hq, Hkv, Sk, Dh = (32, 32, 8192, 192)
        assert Hq % Hkv == 0, (Hq, Hkv)
        return {'x': _w((lambda *s: torch.randn(*s, dtype=torch.bfloat16) * 0.1)(B, Sq, D)), 'k_cache': _w((lambda *s: torch.randn(*s, dtype=torch.bfloat16) * 0.8)(B, Hkv, Sk, Dh)), 'v_cache': _w((lambda *s: torch.randn(*s, dtype=torch.bfloat16) * 3.2)(B, Hkv, Sk, Dh)), 'wq': _w((lambda *s: torch.randn(*s, dtype=torch.bfloat16) * 0.8)(D, Hq * Dh) * D ** (-0.5)), 'wo': _w((lambda *s: torch.randn(*s, dtype=torch.bfloat16) * 3.2)(Hq * Dh, D) * (Hq * Dh) ** (-0.5))}
    _A_in = _A_setup()

    def _B_setup():
        B, S, D, F = (1, 1, 640, 1536)
        return {'x': _w((lambda *s: torch.randn(*s, dtype=torch.bfloat16) * 0.1)(B, S, D)), 'w1': _w((lambda *s: torch.randn(*s, dtype=torch.bfloat16) * 3.2)(D, F) * (2.0 / D) ** 0.5), 'w3': _w((lambda *s: torch.randn(*s, dtype=torch.bfloat16) * 3.2)(D, F) * (2.0 / D) ** 0.5), 'w2': _w((lambda *s: torch.randn(*s, dtype=torch.bfloat16) * 3.2)(F, D) * (2.0 / F) ** 0.5)}
    _B_in = _B_setup()
    return {'A_x': _A_in['x'], 'A_k_cache': _A_in['k_cache'], 'A_v_cache': _A_in['v_cache'], 'A_wq': _A_in['wq'], 'A_wo': _A_in['wo'], 'B_x': _B_in['x'], 'B_w1': _B_in['w1'], 'B_w3': _B_in['w3'], 'B_w2': _B_in['w2'], 'c': _w((lambda *s: torch.randn(*s, dtype=torch.bfloat16) * 0.4)(1, 640) * 8.0), 'w_mod': _w((lambda *s: torch.randn(*s, dtype=torch.bfloat16) * 0.4)(640, 6 * 640) * 640 ** (-0.5) * 8.0)}

def reference(A_x, A_k_cache, A_v_cache, A_wq, A_wo, B_x, B_w1, B_w3, B_w2, c, w_mod):

    def _A_ref(x, k_cache, v_cache, wq, wo):
        B, Sq, D = x.shape
        Hq, Dh = (32, 192)
        Hkv = k_cache.shape[1]
        rep = Hq // Hkv
        q = (lambda x, *d: x.permute(*d))((x @ wq).reshape(B, Sq, Hq, Dh), 0, 2, 1, 3)
        k = (lambda x, n, axis: torch.repeat_interleave(x, n, dim=axis))(k_cache, rep, axis=1)
        v = (lambda x, n, axis: torch.repeat_interleave(x, n, dim=axis))(v_cache, rep, axis=1)
        scores = torch.einsum('bhqd,bhkd->bhqk', q, k) * Dh ** (-0.5)
        p = _softmax(scores, axis=-1)
        o = torch.einsum('bhqk,bhkd->bhqd', p, v)
        return (lambda x, *d: x.permute(*d))(o, 0, 2, 1, 3).reshape(B, Sq, Hq * Dh) @ wo

    def _B_ref(x, w1, w3, w2):
        gate = torch.einsum('bsd,df->bsf', x, w1)
        up = torch.einsum('bsd,df->bsf', x, w3)
        h = _silu(gate) * up
        out = torch.einsum('bsf,fd->bsd', h, w2)
        return out
    x = A_x
    mod = (_silu(c) @ w_mod).reshape(c.shape[0], 6, 1, -1)
    sa, ca, ga, sb, cb, gb = (mod[:, 0].clone(), mod[:, 1].clone(), mod[:, 2].clone(), mod[:, 3].clone(), mod[:, 4].clone(), mod[:, 5].clone())
    h = _layernorm(x, axis=-1) * (1 + ca) + sa
    x = x + ga * _A_ref(h, A_k_cache, A_v_cache, A_wq, A_wo)
    h = _layernorm(x, axis=-1) * (1 + cb) + sb
    x = x + gb * _B_ref(h, B_w1, B_w3, B_w2)
    return x
```

```cpp
#include <cuda_runtime.h>
#include <cuda_bf16.h>
#include <cuda.h>
#include <stdint.h>

namespace {

constexpr int D_MODEL = 640;
constexpr int NH = 32;
constexpr int SK = 8192;
constexpr int DH = 192;
constexpr int FF = 1536;
constexpr int TPH = 128;
constexpr int NS = 8;
constexpr int SLOT_BYTES = 24576;
constexpr int NCW = 8;
constexpr int NTHREADS = (NCW + 1) * 32;
constexpr int WINDOW = 3;
constexpr int NSTATIC = 4;
constexpr int ORE = 4;
constexpr int LAG = 6;

constexpr int N_H1 = 80;
constexpr int N_H3 = 384;
constexpr int N_HEAD = N_H1 + N_H3;
constexpr int N_M = 160;
constexpr int N_WO = 320;
constexpr int NK = NH * TPH;
constexpr int NSEQ = NK + NK + N_WO + N_M;

constexpr int N_F1 = 96;
constexpr int N_F2 = 40;

enum { T_K = 1, T_V = 2, T_WO = 3, T_M = 4, T_Q = 5, T_END = 15 };

struct __align__(128) Ctr { unsigned v; unsigned pad[31]; };
struct __align__(128) Acc {
  Ctr ticket, cntH1, cntH3, cntM, cntWO;
  Ctr cntK[NH], cntV[NH];
  float mod[6 * D_MODEL];
  float q[NH * DH];
  float o[NH][ORE][DH];
  float attn[D_MODEL];
};
static_assert(sizeof(Acc) % 16 == 0, "");

__device__ Acc g_acc[2];
__device__ unsigned g_epoch;
__device__ __align__(128) __nv_bfloat16 g_scores[NH * SK];
__device__ __align__(128) float2 g_tstat[NH * TPH];
__device__ __align__(128) float4 g_hstat[NH];
__device__ __align__(128) uint2 g_llhh[FF / 2];

#define PROF_STAMP(i) do {} while (0)

constexpr int SM_SLOTS = 0;
constexpr int SM_SIDE = SM_SLOTS + NS * SLOT_BYTES;
constexpr int SM_STAGE = SM_SIDE + NS * 256;
constexpr int SM_Q = SM_STAGE + NCW * 512;
constexpr int SM_VA = SM_Q + NH * DH * 2;
constexpr int SM_VH = SM_VA + D_MODEL * 2;
constexpr int SM_X = SM_VH + D_MODEL * 2;
constexpr int SM_RED = SM_X + D_MODEL * 4;
constexpr int SM_BAR = SM_RED + NCW * 32 * 4;
constexpr int SM_DESC = SM_BAR + 20 * 8;
constexpr int SM_TOTAL = SM_DESC + 64;
constexpr int SM_HH = SM_Q;
constexpr int SM_MOD = SM_Q + FF * 2;
static_assert(FF * 2 + 4 * D_MODEL * 2 <= NH * DH * 2, "");
static_assert(SM_TOTAL <= 232448, "");

struct Params {
  const __nv_bfloat16* x;
  const __nv_bfloat16* c;
  __nv_bfloat16* out;
};

__device__ __forceinline__ uint32_t smem_u32(const void* p) { return (uint32_t)__cvta_generic_to_shared(p); }
__device__ __forceinline__ void mbar_init(uint32_t bar, uint32_t cnt) {
  asm volatile("mbarrier.init.shared::cta.b64 [%0], %1;" ::"r"(bar), "r"(cnt) : "memory");
}
__device__ __forceinline__ void mbar_expect_tx(uint32_t bar, uint32_t bytes) {
  asm volatile("mbarrier.arrive.expect_tx.shared::cta.b64 _, [%0], %1;" ::"r"(bar), "r"(bytes) : "memory");
}
__device__ __forceinline__ void mbar_arrive(uint32_t bar) {
  asm volatile("mbarrier.arrive.shared::cta.b64 _, [%0];" ::"r"(bar) : "memory");
}
__device__ __forceinline__ bool mbar_try(uint32_t bar, uint32_t parity) {
  uint32_t ok;
  asm volatile(
      "{\n.reg .pred p;\nmbarrier.try_wait.parity.shared::cta.b64 p, [%1], %2;\nselp.u32 %0, 1, 0, p;\n}"
      : "=r"(ok) : "r"(bar), "r"(parity) : "memory");
  return ok != 0;
}
__device__ __forceinline__ bool mbar_test(uint32_t bar, uint32_t parity) {
  uint32_t ok;
  asm volatile(
      "{\n.reg .pred p;\nmbarrier.test_wait.parity.shared::cta.b64 p, [%1], %2;\nselp.u32 %0, 1, 0, p;\n}"
      : "=r"(ok) : "r"(bar), "r"(parity) : "memory");
  return ok != 0;
}
__device__ __forceinline__ void mbar_wait(uint32_t bar, uint32_t parity) {
  uint32_t it = 0;
  while (!mbar_try(bar, parity)) {
    if (++it > (1u << 24)) __trap();
  }
}
__device__ __forceinline__ void tma_2d(uint32_t dst, const CUtensorMap* tm, int c0, int c1, uint32_t bar, uint64_t pol) {
  asm volatile(
      "cp.async.bulk.tensor.2d.shared::cluster.global.mbarrier::complete_tx::bytes.L2::cache_hint [%0], [%1, {%3, %4}], [%2], %5;"
      ::"r"(dst), "l"(tm), "r"(bar), "r"(c0), "r"(c1), "l"(pol) : "memory");
}
__device__ __forceinline__ void tma_3d(uint32_t dst, const CUtensorMap* tm, int c0, int c1, int c2, uint32_t bar) {
  asm volatile(
      "cp.async.bulk.tensor.3d.shared::cluster.global.mbarrier::complete_tx::bytes [%0], [%1, {%3, %4, %5}], [%2];"
      ::"r"(dst), "l"(tm), "r"(bar), "r"(c0), "r"(c1), "r"(c2) : "memory");
}
__device__ __forceinline__ void bulk_g2s(uint32_t dst, const void* src, uint32_t bytes, uint32_t bar) {
  asm volatile("cp.async.bulk.shared::cluster.global.mbarrier::complete_tx::bytes [%0], [%1], %2, [%3];"
               ::"r"(dst), "l"(src), "r"(bytes), "r"(bar) : "memory");
}
__device__ __forceinline__ void prefetch_tm(const CUtensorMap* tm) {
  asm volatile("prefetch.tensormap [%0];" ::"l"(tm) : "memory");
}
__device__ __forceinline__ void ldsm4(uint32_t (&a)[4], uint32_t addr) {
  asm volatile("ldmatrix.sync.aligned.m8n8.x4.shared.b16 {%0,%1,%2,%3}, [%4];"
               : "=r"(a[0]), "=r"(a[1]), "=r"(a[2]), "=r"(a[3]) : "r"(addr) : "memory");
}
__device__ __forceinline__ void ldsm4t(uint32_t (&a)[4], uint32_t addr) {
  asm volatile("ldmatrix.sync.aligned.m8n8.x4.trans.shared.b16 {%0,%1,%2,%3}, [%4];"
               : "=r"(a[0]), "=r"(a[1]), "=r"(a[2]), "=r"(a[3]) : "r"(addr) : "memory");
}
__device__ __forceinline__ void mma16816(float (&d)[4], const uint32_t (&a)[4], uint32_t b0, uint32_t b1) {
  asm volatile(
      "mma.sync.aligned.m16n8k16.row.col.f32.bf16.bf16.f32 {%0,%1,%2,%3}, {%4,%5,%6,%7}, {%8,%9}, {%0,%1,%2,%3};"
      : "+f"(d[0]), "+f"(d[1]), "+f"(d[2]), "+f"(d[3])
      : "r"(a[0]), "r"(a[1]), "r"(a[2]), "r"(a[3]), "r"(b0), "r"(b1));
}
__device__ __forceinline__ unsigned ld_acquire(const unsigned* p) {
  unsigned v;
  asm volatile("ld.acquire.gpu.global.u32 %0, [%1];" : "=r"(v) : "l"(p) : "memory");
  return v;
}
__device__ __forceinline__ uint2 ld_relaxed_v2(const uint2* p) {
  uint2 v;
  asm volatile("ld.relaxed.gpu.global.v2.u32 {%0,%1}, [%2];" : "=r"(v.x), "=r"(v.y) : "l"(p) : "memory");
  return v;
}
__device__ __forceinline__ void st_relaxed_v2(uint2* p, uint2 v) {
  asm volatile("st.relaxed.gpu.global.v2.u32 [%0], {%1,%2};" ::"l"(p), "r"(v.x), "r"(v.y) : "memory");
}
__device__ __forceinline__ void st_relaxed(unsigned* p, unsigned v) {
  asm volatile("st.relaxed.gpu.global.u32 [%0], %1;" ::"l"(p), "r"(v) : "memory");
}
__device__ __forceinline__ void fence_gpu() { asm volatile("fence.acq_rel.gpu;" ::: "memory"); }
__device__ __forceinline__ void red_add_f32(float* p, float v) {
  asm volatile("red.relaxed.gpu.global.add.f32 [%0], %1;" ::"l"(p), "f"(v) : "memory");
}
__device__ __forceinline__ void red_add_u32(unsigned* p, unsigned v) {
  asm volatile("red.relaxed.gpu.global.add.u32 [%0], %1;" ::"l"(p), "r"(v) : "memory");
}
__device__ __forceinline__ void spin_ge(const unsigned* p, unsigned target) {
  uint32_t it = 0;
  while (ld_acquire(p) < target) {
    if (++it > (1u << 22)) __trap();
  }
}
__device__ __forceinline__ void cons_bar() { asm volatile("bar.sync 1, 256;" ::: "memory"); }

__device__ __forceinline__ float bf16r(float x) { return __bfloat162float(__float2bfloat16_rn(x)); }
__device__ __forceinline__ uint32_t pack_bf16(float lo, float hi) {
  __nv_bfloat162 v = __floats2bfloat162_rn(lo, hi);
  return *reinterpret_cast<uint32_t*>(&v);
}
__device__ __forceinline__ float bf_lo(uint32_t v) { return __uint_as_float(v << 16); }
__device__ __forceinline__ float bf_hi(uint32_t v) { return __uint_as_float(v & 0xffff0000u); }
__device__ __forceinline__ float warp_sum(float v) {
#pragma unroll
  for (int o = 16; o > 0; o >>= 1) v += __shfl_xor_sync(0xffffffffu, v, o);
  return v;
}
__device__ __forceinline__ float warp_max(float v) {
#pragma unroll
  for (int o = 16; o > 0; o >>= 1) v = fmaxf(v, __shfl_xor_sync(0xffffffffu, v, o));
  return v;
}
__device__ __forceinline__ float fast_exp(float x) {
  float r;
  asm("ex2.approx.ftz.f32 %0, %1;" : "=f"(r) : "f"(x * 1.4426950408889634f));
  return r;
}
__device__ __forceinline__ float silu_f(float x) { return x / (1.0f + expf(-x)); }
__device__ __forceinline__ float sel4(int j, float a, float b, float c, float d) {
  float lo = (j & 1) ? b : a, hi = (j & 1) ? d : c;
  return (j & 2) ? hi : lo;
}

template <int KS>
__device__ __forceinline__ void gemv_tile(uint32_t slot, const uint32_t* vec32, float* dst, int lane,
                                          uint32_t release_bar) {
  const int g = lane >> 2, j = lane & 3;
  const int r0 = (lane & 7) + ((lane >> 4) << 3), lo = (lane >> 3) & 1;
  const uint32_t vg = slot + r0 * 128 + ((lo ^ (r0 & 7)) << 4);
  float acc[4][4];
#pragma unroll
  for (int m = 0; m < 4; m++) { acc[m][0] = acc[m][1] = acc[m][2] = acc[m][3] = 0.f; }
#pragma unroll
  for (int ks = 0; ks < KS; ks++) {
    const uint32_t b0 = vec32[8 * ks + j], b1 = vec32[8 * ks + 4 + j];
#pragma unroll
    for (int m = 0; m < 4; m++) {
      uint32_t a[4];
      ldsm4t(a, (vg + ks * 2048) ^ (m << 5));
      mma16816(acc[m], a, b0, b1);
    }
  }
  __syncwarp();
  if (lane == 0) mbar_arrive(release_bar);
  const float v0 = sel4(j, acc[0][0], acc[1][0], acc[2][0], acc[3][0]);
  const float v1 = sel4(j, acc[0][2], acc[1][2], acc[2][2], acc[3][2]);
  red_add_f32(dst + 16 * j + g, v0);
  red_add_f32(dst + 16 * j + 8 + g, v1);
}

__device__ __forceinline__ void signal(unsigned* ctr, int lane) {
  __syncwarp();
  if (lane == 0) { fence_gpu(); red_add_u32(ctr, 1u); }
}

__device__ __forceinline__ void ln_stats(const float* xs, int lane, float& mean_b, float& sd_b) {
  float v[20];
  float s = 0.f;
#pragma unroll
  for (int i = 0; i < 20; i++) { v[i] = xs[lane + 32 * i]; s += v[i]; }
  const float mean = warp_sum(s) * (1.0f / D_MODEL);
  float s2 = 0.f;
#pragma unroll
  for (int i = 0; i < 20; i++) { const float d = v[i] - mean; s2 += d * d; }
  const float var = warp_sum(s2) * (1.0f / D_MODEL);
  mean_b = bf16r(mean);
  sd_b = bf16r(sqrtf(bf16r(bf16r(var) + 1e-5f)));
}
__device__ __forceinline__ float ln_mod(float x, float mean_b, float sd_b, float cmul, float sadd) {
  const float a = bf16r(x - mean_b);
  const float n = bf16r(a / sd_b);
  return bf16r(bf16r(n * bf16r(1.0f + cmul)) + sadd);
}

__global__ void __launch_bounds__(NTHREADS, 1)
fused_kernel(const __grid_constant__ CUtensorMap tmK, const __grid_constant__ CUtensorMap tmV,
             const __grid_constant__ CUtensorMap tmWq, const __grid_constant__ CUtensorMap tmWmod,
             const __grid_constant__ CUtensorMap tmWo, const __grid_constant__ CUtensorMap tmW1,
             const __grid_constant__ CUtensorMap tmW3, const __grid_constant__ CUtensorMap tmW2,
             const Params prm) {
  extern __shared__ __align__(1024) unsigned char smem[];
  const uint32_t sb = smem_u32(smem);
  const int tid = threadIdx.x, warp = tid >> 5, lane = tid & 31;
  const int cta = blockIdx.x, G = gridDim.x;
  const uint32_t bar_full = sb + SM_BAR, bar_empty = bar_full + NS * 8, bar_tail = bar_empty + NS * 8;
  volatile uint32_t* desc = reinterpret_cast<volatile uint32_t*>(smem + SM_DESC);
  volatile uint32_t* tailslot = desc + 8;
  volatile uint32_t* s_epoch = desc + 12;
  const int nh = (N_HEAD - cta + G - 1) / G;
  const bool has_f1 = cta < N_F1;
  const int f2 = G - 1 - cta;
  const bool has_f2 = f2 < N_F2;

  if (warp == NCW) {
    if (lane == 0) {
      PROF_STAMP(0);
      for (int i = 0; i < NS; i++) { mbar_init(bar_full + 8 * i, 1); mbar_init(bar_empty + 8 * i, 1); }
      for (int i = 0; i < 4; i++) mbar_init(bar_tail + 8 * i, 1);
      asm volatile("fence.mbarrier_init.release.cluster;" ::: "memory");
      asm volatile("fence.proxy.async.shared::cta;" ::: "memory");
      uint64_t pol;
      asm volatile("createpolicy.fractional.L2::evict_first.b64 %0, 1.0;" : "=l"(pol));
      for (int i = 0; i < nh; i++) {
        const int id = cta + i * G;
        const uint32_t bar = bar_full + 8 * i;
        mbar_expect_tx(bar, 160 * 128);
        if (id < N_H1) {
          desc[i] = (T_M << 28) | ((id & 3) << 16) | (id >> 2);
          tma_2d(sb + i * SLOT_BYTES, &tmWmod, (id >> 2) * 64, (id & 3) * 160, bar, pol);
        } else {
          const int q = id - N_H1;
          desc[i] = (T_Q << 28) | ((q & 3) << 16) | (q >> 2);
          tma_2d(sb + i * SLOT_BYTES, &tmWq, (q >> 2) * 64, (q & 3) * 160, bar, pol);
        }
      }
      prefetch_tm(&tmK);
      prefetch_tm(&tmV);
      prefetch_tm(&tmWo);
    }
  } else {
    if (tid == 0) *s_epoch = *reinterpret_cast<volatile unsigned*>(&g_epoch);
    uint32_t* va = reinterpret_cast<uint32_t*>(smem + SM_VA);
    float* xs = reinterpret_cast<float*>(smem + SM_X);
    for (int p = tid; p < D_MODEL / 2; p += 256) {
      const uint32_t cv = reinterpret_cast<const uint32_t*>(prm.c)[p];
      const uint32_t xv = reinterpret_cast<const uint32_t*>(prm.x)[p];
      va[p] = pack_bf16(silu_f(bf_lo(cv)), silu_f(bf_hi(cv)));
      xs[2 * p] = bf_lo(xv);
      xs[2 * p + 1] = bf_hi(xv);
    }
  }
  __syncthreads();
  const unsigned ep = *s_epoch;
  const unsigned tag = ep + 1;
  Acc* acc = &g_acc[ep & 1];

  if (warp == NCW) {
    uint64_t pol;
    asm volatile("createpolicy.fractional.L2::evict_first.b64 %0, 1.0;" : "=l"(pol));
    uint32_t tkA = 0, tkB = 0;
    if (lane == 0) { tkA = atomicAdd(&acc->ticket.v, 1u); tkB = atomicAdd(&acc->ticket.v, 1u); }
    uint32_t ready = 0;
    int n = nh, istat = 0;
    for (;;) {
      uint32_t seq;
      if (istat < NSTATIC) {
        seq = cta + G * istat;
        istat++;
      } else {
        seq = NSTATIC * G + __shfl_sync(0xffffffffu, tkA, 0);
        tkA = tkB;
        if (seq < NSEQ && lane == 0) tkB = atomicAdd(&acc->ticket.v, 1u);
      }
      if (seq >= NSEQ) break;
      int type, a, b;
      if (seq < NK) {
        type = T_K; a = seq >> 7; b = seq & 127;
      } else {
        uint32_t r = seq - NK;
        if (r < LAG * TPH) {
          type = T_V; a = r >> 7; b = r & 127;
        } else {
          r -= LAG * TPH;
          const uint32_t blk = r / 138u, off = r - blk * 138u;
          if (blk < NH - LAG) {
            if (off < TPH) { type = T_V; a = LAG + blk; b = off; }
            else { type = T_WO; a = blk; b = off - TPH; }
          } else {
            r -= (NH - LAG) * 138u;
            if (r < LAG * 10) { type = T_WO; a = NH - LAG + r / 10u; b = r % 10u; }
            else { r -= LAG * 10; type = T_M; a = r & 3; b = 20 + (r >> 2); }
          }
        }
      }
      const int slot = n & (NS - 1), use = n >> 3;
      if (type == T_V && !((ready >> a) & 1u)) {
        uint32_t it = 0;
        do {
          const unsigned t = ld_acquire(reinterpret_cast<const unsigned*>(&g_hstat[lane].z));
          ready = __ballot_sync(0xffffffffu, t == tag);
          if (++it > (1u << 22)) __trap();
        } while (!((ready >> a) & 1u));
        __syncwarp();
        asm volatile("fence.proxy.async;" ::: "memory");
      }
      if (lane == 0) {
        if (use > 0) mbar_wait(bar_empty + 8 * slot, (use - 1) & 1);
        if (n >= WINDOW) mbar_wait(bar_full + 8 * ((n - WINDOW) & (NS - 1)), ((n - WINDOW) >> 3) & 1);
        const uint32_t bar = bar_full + 8 * slot, dst = sb + slot * SLOT_BYTES;
        desc[slot] = ((uint32_t)type << 28) | (a << 16) | b;
        if (type == T_K) {
          mbar_expect_tx(bar, SLOT_BYTES);
          tma_2d(dst, &tmK, 0, (a * TPH + b) * 192, bar, pol);
        } else if (type == T_V) {
          mbar_expect_tx(bar, SLOT_BYTES + 128 + 16);
          tma_2d(dst, &tmV, 0, (a * TPH + b) * 192, bar, pol);
          bulk_g2s(sb + SM_SIDE + slot * 256, g_scores + a * SK + b * 64, 128, bar);
          bulk_g2s(sb + SM_SIDE + slot * 256 + 128, &g_hstat[a], 16, bar);
        } else if (type == T_WO) {
          mbar_expect_tx(bar, 192 * 128);
          tma_2d(dst, &tmWo, b * 64, a * DH, bar, pol);
        } else {
          mbar_expect_tx(bar, 160 * 128);
          tma_2d(dst, &tmWmod, b * 64, a * 160, bar, pol);
        }
      }
      __syncwarp();
      n++;
    }
    if (lane == 0) {
      PROF_STAMP(8);
      uint32_t pending = (1u << NS) - 1;
      int ti = 0;
      uint32_t it = 0;
      while (pending) {
        for (int k = 0; k < NS; k++) {
          const int nn = n + k, s = nn & (NS - 1), use = nn >> 3;
          if (!((pending >> s) & 1u)) continue;
          if (use > 0 && !mbar_test(bar_empty + 8 * s, (use - 1) & 1)) continue;
          pending &= ~(1u << s);
          while (ti < 4 && !((ti < 2) ? has_f1 : has_f2)) ti++;
          if (ti < 4) {
            const uint32_t dst = sb + s * SLOT_BYTES, bar = bar_tail + 8 * ti;
            tailslot[ti] = s;
            if (ti < 2) {
              mbar_expect_tx(bar, D_MODEL * 32);
              tma_3d(dst, ti == 0 ? &tmW1 : &tmW3, cta * 16, 0, 0, bar);
            } else {
              mbar_expect_tx(bar, 768 * 32);
              tma_3d(dst, &tmW2, f2 * 16, 0, (ti - 2) * 3, bar);
            }
            ti++;
          }
          desc[s] = (uint32_t)T_END << 28;
          mbar_arrive(bar_full + 8 * s);
        }
        if (++it > (1u << 24)) __trap();
      }
    }
    return;
  }

  const int g = lane >> 2, j = lane & 3;
  float* xs = reinterpret_cast<float*>(smem + SM_X);

  {
    uint4* nx = reinterpret_cast<uint4*>(&g_acc[(ep & 1) ^ 1]);
    constexpr int NZ = sizeof(Acc) / 16;
    for (int i = cta * 256 + tid; i < NZ; i += G * 256) nx[i] = make_uint4(0, 0, 0, 0);
  }

  {
    float mean_b, sd_b;
    ln_stats(xs, lane, mean_b, sd_b);
    const uint32_t my_desc = (warp < nh) ? desc[warp] : 0u;
    const int my_type = my_desc >> 28, ra = (my_desc >> 16) & 0xfff, rb = my_desc & 0xffff;
    if (warp < nh && my_type == T_M) {
      mbar_wait(bar_full + 8 * warp, 0);
      gemv_tile<10>(sb + warp * SLOT_BYTES, reinterpret_cast<const uint32_t*>(smem + SM_VA) + ra * 80,
                    acc->mod + rb * 64, lane, bar_empty + 8 * warp);
      signal(&acc->cntH1.v, lane);
    }
    if (tid == 0) { spin_ge(&acc->cntH1.v, N_H1); PROF_STAMP(1); }
    cons_bar();
    uint32_t* vh = reinterpret_cast<uint32_t*>(smem + SM_VH);
    for (int p = tid; p < D_MODEL / 2; p += 256) {
      const float2 sa = __ldcg(reinterpret_cast<const float2*>(acc->mod) + p);
      const float2 ca = __ldcg(reinterpret_cast<const float2*>(acc->mod + D_MODEL) + p);
      const float h0 = ln_mod(xs[2 * p], mean_b, sd_b, bf16r(ca.x), bf16r(sa.x));
      const float h1 = ln_mod(xs[2 * p + 1], mean_b, sd_b, bf16r(ca.y), bf16r(sa.y));
      vh[p] = pack_bf16(h0, h1);
    }
    cons_bar();
    if (warp < nh && my_type == T_Q) {
      mbar_wait(bar_full + 8 * warp, 0);
      gemv_tile<10>(sb + warp * SLOT_BYTES, reinterpret_cast<const uint32_t*>(smem + SM_VH) + ra * 80,
                    acc->q + rb * 64, lane, bar_empty + 8 * warp);
      signal(&acc->cntH3.v, lane);
    }
    if (tid == 0) {
      spin_ge(&acc->cntH3.v, N_H3);
      if (cta == 0) g_epoch = ep + 1;
      PROF_STAMP(2);
    }
    cons_bar();
    uint2* qs = reinterpret_cast<uint2*>(smem + SM_Q);
#pragma unroll
    for (int i = 0; i < 6; i++) {
      const float4 v = __ldcg(reinterpret_cast<const float4*>(acc->q) + i * 256 + tid);
      qs[i * 256 + tid] = make_uint2(pack_bf16(v.x, v.y), pack_bf16(v.z, v.w));
    }
    cons_bar();
    if (tid == 0) PROF_STAMP(3);
  }

  {
    const uint32_t slot = sb + warp * SLOT_BYTES;
    const uint32_t my_full = bar_full + 8 * warp, my_empty = bar_empty + 8 * warp;
    uint32_t* stage = reinterpret_cast<uint32_t*>(smem + SM_STAGE + warp * 512);
    const uint32_t* side = reinterpret_cast<const uint32_t*>(smem + SM_SIDE + warp * 256);
    uint32_t vk[3], vv[3];
    {
      const int r0 = (lane & 7) + (((lane >> 3) & 1) << 3), hi = lane >> 4;
      const int r1 = (lane & 7) + ((lane >> 4) << 3), lo = (lane >> 3) & 1;
#pragma unroll
      for (int t = 0; t < 3; t++) {
        vk[t] = slot + (3 * r0 + t) * 128 + ((hi ^ ((3 * r0 + t) & 7)) << 4);
        vv[t] = slot + (3 * r1 + t) * 128 + ((lo ^ ((3 * r1 + t) & 7)) << 4);
      }
    }
    uint32_t use = (warp < nh) ? 1 : 0;
    for (;; use++) {
      mbar_wait(my_full, use & 1);
      const uint32_t d = desc[warp];
      const int type = d >> 28, a = (d >> 16) & 0xfff, b = d & 0xffff;
      if (type == T_K) {
        const uint32_t* q32 = reinterpret_cast<const uint32_t*>(smem + SM_Q) + a * (DH / 2);
        float s[4][4];
#pragma unroll
        for (int m = 0; m < 4; m++) { s[m][0] = s[m][1] = s[m][2] = s[m][3] = 0.f; }
#pragma unroll
        for (int ks = 0; ks < 12; ks++) {
          const uint32_t b0 = q32[8 * ks + j], b1 = q32[8 * ks + 4 + j];
#pragma unroll
          for (int m = 0; m < 4; m++) {
            uint32_t af[4];
            ldsm4(af, (vk[ks >> 2] ^ ((ks & 3) << 5)) + m * 6144);
            mma16816(s[m], af, b0, b1);
          }
        }
        __syncwarp();
        if (lane == 0) mbar_arrive(my_empty);
        const float scale = 0.07216878364870323f;
        const float s0 = bf16r(bf16r(sel4(j, s[0][0], s[1][0], s[2][0], s[3][0])) * scale);
        const float s1 = bf16r(bf16r(sel4(j, s[0][2], s[1][2], s[2][2], s[3][2])) * scale);
        __nv_bfloat16* st16 = reinterpret_cast<__nv_bfloat16*>(stage);
        st16[16 * j + g] = __float2bfloat16_rn(s0);
        st16[16 * j + 8 + g] = __float2bfloat16_rn(s1);
        __syncwarp();
        const uint32_t pr = stage[lane];
        reinterpret_cast<uint32_t*>(g_scores)[a * (SK / 2) + b * 32 + lane] = pr;
        const float e0 = bf_lo(pr), e1 = bf_hi(pr);
        const float tmax = warp_max(fmaxf(e0, e1));
        const float tsum = warp_sum(fast_exp(e0 - tmax) + fast_exp(e1 - tmax));
        unsigned old = 0;
        if (lane == 0) g_tstat[a * TPH + b] = make_float2(tmax, tsum);
        __syncwarp();
        if (lane == 0) {
          fence_gpu();
          old = atomicAdd(&acc->cntK[a].v, 1u);
        }
        old = __shfl_sync(0xffffffffu, old, 0);
        if (old == TPH - 1) {
          fence_gpu();
          const float4 t0 = __ldcg(reinterpret_cast<const float4*>(g_tstat + a * TPH) + lane);
          const float4 t1 = __ldcg(reinterpret_cast<const float4*>(g_tstat + a * TPH) + 32 + lane);
          const float m = warp_max(fmaxf(fmaxf(t0.x, t0.z), fmaxf(t1.x, t1.z)));
          const float l = warp_sum(t0.y * fast_exp(t0.x - m) + t0.w * fast_exp(t0.z - m) +
                                   t1.y * fast_exp(t1.x - m) + t1.w * fast_exp(t1.z - m));
          if (lane == 0) {
            g_hstat[a].x = m;
            g_hstat[a].y = 1.0f / l;
            fence_gpu();
            st_relaxed(reinterpret_cast<unsigned*>(&g_hstat[a].z), tag);
          }
        }
      } else if (type == T_V) {
        {
          const uint32_t pr = side[lane];
          const float m = __uint_as_float(side[32]), inv = __uint_as_float(side[33]);
          stage[lane] = pack_bf16(fast_exp(bf_lo(pr) - m) * inv, fast_exp(bf_hi(pr) - m) * inv);
        }
        __syncwarp();
        float o[12][4];
#pragma unroll
        for (int m = 0; m < 12; m++) { o[m][0] = o[m][1] = o[m][2] = o[m][3] = 0.f; }
#pragma unroll
        for (int ks = 0; ks < 4; ks++) {
          const uint32_t b0 = stage[8 * ks + j], b1 = stage[8 * ks + 4 + j];
#pragma unroll
          for (int m = 0; m < 12; m++) {
            uint32_t af[4];
            ldsm4t(af, (vv[m >> 2] ^ ((m & 3) << 5)) + ks * 6144);
            mma16816(o[m], af, b0, b1);
          }
        }
        __syncwarp();
        if (lane == 0) mbar_arrive(my_empty);
        float* dst = acc->o[a][cta & (ORE - 1)];
#pragma unroll
        for (int i = 0; i < 3; i++) {
          red_add_f32(dst + 16 * (4 * i + j) + g, sel4(j, o[4 * i][0], o[4 * i + 1][0], o[4 * i + 2][0], o[4 * i + 3][0]));
          red_add_f32(dst + 16 * (4 * i + j) + 8 + g, sel4(j, o[4 * i][2], o[4 * i + 1][2], o[4 * i + 2][2], o[4 * i + 3][2]));
        }
        signal(&acc->cntV[a].v, lane);
      } else if (type == T_WO) {
        if (lane == 0) spin_ge(&acc->cntV[a].v, TPH);
        __syncwarp();
#pragma unroll
        for (int i = 0; i < 3; i++) {
          float2 v = make_float2(0.f, 0.f);
#pragma unroll
          for (int r = 0; r < ORE; r++) {
            const float2 t = __ldcg(reinterpret_cast<const float2*>(acc->o[a][r]) + i * 32 + lane);
            v.x += t.x; v.y += t.y;
          }
          stage[i * 32 + lane] = pack_bf16(v.x, v.y);
        }
        __syncwarp();
        gemv_tile<12>(slot, stage, acc->attn + b * 64, lane, my_empty);
        signal(&acc->cntWO.v, lane);
      } else if (type == T_M) {
        gemv_tile<10>(slot, reinterpret_cast<const uint32_t*>(smem + SM_VA) + a * 80, acc->mod + b * 64, lane, my_empty);
        signal(&acc->cntM.v, lane);
      } else {
        break;
      }
    }
  }

  cons_bar();
  if (tid == 0) PROF_STAMP(9);
  uint32_t* modb = reinterpret_cast<uint32_t*>(smem + SM_MOD);
  if (tid == 0) spin_ge(&acc->cntM.v, N_M);
  cons_bar();
  for (int p = tid; p < 4 * D_MODEL / 2; p += 256) {
    const float2 v = __ldcg(reinterpret_cast<const float2*>(acc->mod + 2 * D_MODEL) + p);
    modb[p] = pack_bf16(v.x, v.y);
  }
  if (tid == 0) { spin_ge(&acc->cntWO.v, N_WO); PROF_STAMP(10); }
  cons_bar();
  for (int p = tid; p < D_MODEL / 2; p += 256) {
    const float2 at = __ldcg(reinterpret_cast<const float2*>(acc->attn) + p);
    const uint32_t ga = modb[p];
    xs[2 * p] = bf16r(xs[2 * p] + bf16r(bf_lo(ga) * bf16r(at.x)));
    xs[2 * p + 1] = bf16r(xs[2 * p + 1] + bf16r(bf_hi(ga) * bf16r(at.y)));
  }
  cons_bar();
  float* red = reinterpret_cast<float*>(smem + SM_RED);
  if (has_f1) {
    float mean_b, sd_b;
    ln_stats(xs, lane, mean_b, sd_b);
    uint32_t* vh = reinterpret_cast<uint32_t*>(smem + SM_VH);
    for (int p = 40 * warp + lane; p < 40 * warp + 40; p += 32) {
      const uint32_t sbv = modb[320 + p], cbv = modb[640 + p];
      vh[p] = pack_bf16(ln_mod(xs[2 * p], mean_b, sd_b, bf_lo(cbv), bf_lo(sbv)),
                        ln_mod(xs[2 * p + 1], mean_b, sd_b, bf_hi(cbv), bf_hi(sbv)));
    }
    __syncwarp();
    mbar_wait(bar_tail + 0, 0);
    mbar_wait(bar_tail + 8, 0);
    const int r0 = (lane & 7) + ((lane >> 4) << 3), lo = (lane >> 3) & 1;
    const uint32_t off = (warp * 80 + r0) * 32 + ((lo ^ ((r0 >> 2) & 1)) << 4);
    const uint32_t w1 = sb + tailslot[0] * SLOT_BYTES + off, w3 = sb + tailslot[1] * SLOT_BYTES + off;
    float ga[4] = {0.f, 0.f, 0.f, 0.f}, ua[4] = {0.f, 0.f, 0.f, 0.f};
#pragma unroll
    for (int ks = 0; ks < 5; ks++) {
      const uint32_t b0 = vh[40 * warp + 8 * ks + j], b1 = vh[40 * warp + 8 * ks + 4 + j];
      uint32_t af[4];
      ldsm4t(af, w1 + ks * 512);
      mma16816(ga, af, b0, b1);
      ldsm4t(af, w3 + ks * 512);
      mma16816(ua, af, b0, b1);
    }
    if (j == 0) {
      red[warp * 32 + g] = ga[0];
      red[warp * 32 + 8 + g] = ga[2];
      red[warp * 32 + 16 + g] = ua[0];
      red[warp * 32 + 24 + g] = ua[2];
    }
    cons_bar();
    if (warp == 0) {
      float v = 0.f;
#pragma unroll
      for (int w = 0; w < NCW; w++) v += red[w * 32 + lane];
      v = bf16r(v);
      const float up = __shfl_down_sync(0xffffffffu, v, 16);
      const float hh = bf16r(bf16r(silu_f(v)) * up);
      const float hn = __shfl_down_sync(0xffffffffu, hh, 1);
      if (lane < 16 && !(lane & 1)) st_relaxed_v2(&g_llhh[cta * 8 + (lane >> 1)], make_uint2(pack_bf16(hh, hn), tag));
      if (lane == 0) PROF_STAMP(11);
    }
  }
  if (has_f2) {
    uint32_t* hh = reinterpret_cast<uint32_t*>(smem + SM_HH);
#pragma unroll
    for (int i = 0; i < 3; i++) {
      uint2 v;
      uint32_t it = 0;
      do {
        v = ld_relaxed_v2(&g_llhh[i * 256 + tid]);
        if (++it > (1u << 22)) __trap();
      } while (v.y != tag);
      hh[i * 256 + tid] = v.x;
    }
    cons_bar();
    if (tid == 0) PROF_STAMP(12);
    mbar_wait(bar_tail + 16, 0);
    mbar_wait(bar_tail + 24, 0);
    const int r0 = (lane & 7) + ((lane >> 4) << 3), lo = (lane >> 3) & 1;
    const uint32_t w2 = sb + tailslot[2 + (warp >> 2)] * SLOT_BYTES + ((warp & 3) * 192 + r0) * 32 +
                        ((lo ^ ((r0 >> 2) & 1)) << 4);
    float oa[4] = {0.f, 0.f, 0.f, 0.f}, ob[4] = {0.f, 0.f, 0.f, 0.f};
#pragma unroll
    for (int ks = 0; ks < 12; ks += 2) {
      uint32_t af[4];
      ldsm4t(af, w2 + ks * 512);
      mma16816(oa, af, hh[96 * warp + 8 * ks + j], hh[96 * warp + 8 * ks + 4 + j]);
      ldsm4t(af, w2 + (ks + 1) * 512);
      mma16816(ob, af, hh[96 * warp + 8 * ks + 8 + j], hh[96 * warp + 8 * ks + 12 + j]);
    }
    if (j == 0) {
      red[warp * 32 + g] = oa[0] + ob[0];
      red[warp * 32 + 8 + g] = oa[2] + ob[2];
    }
    cons_bar();
    if (tid < 16) {
      float v = 0.f;
#pragma unroll
      for (int w = 0; w < NCW; w++) v += red[w * 32 + tid];
      const int col = f2 * 16 + tid;
      const uint32_t gbp = modb[960 + (col >> 1)];
      const float gb = (col & 1) ? bf_hi(gbp) : bf_lo(gbp);
      prm.out[col] = __float2bfloat16_rn(xs[col] + bf16r(gb * bf16r(v)));
    }
    if (tid == 0) PROF_STAMP(13);
  }
}

typedef CUresult (*EncodeFn)(CUtensorMap*, CUtensorMapDataType, cuuint32_t, void*, const cuuint64_t*,
                             const cuuint64_t*, const cuuint32_t*, const cuuint32_t*, CUtensorMapInterleave,
                             CUtensorMapSwizzle, CUtensorMapL2promotion, CUtensorMapFloatOOBfill);

void make_map(EncodeFn fn, CUtensorMap* tm, const void* base, int rank, const cuuint64_t* dims,
              const cuuint64_t* strides, const cuuint32_t* box, CUtensorMapSwizzle sw, CUtensorMapL2promotion pr) {
  cuuint32_t es[3] = {1, 1, 1};
  fn(tm, CU_TENSOR_MAP_DATA_TYPE_BFLOAT16, rank, const_cast<void*>(base), dims, strides, box, es,
     CU_TENSOR_MAP_INTERLEAVE_NONE, sw, pr, CU_TENSOR_MAP_FLOAT_OOB_FILL_NONE);
}

}

extern "C" void kernel_launch(void* const* d_in, const int* in_sizes, int n_in, void* d_out, int out_size) {
  (void)in_sizes; (void)n_in; (void)out_size;
  static EncodeFn encode = nullptr;
  static int num_sms = 0;
  if (!encode) {
    void* fn = nullptr;
    cudaDriverEntryPointQueryResult qr;
    cudaGetDriverEntryPoint("cuTensorMapEncodeTiled", &fn, cudaEnableDefault, &qr);
    encode = reinterpret_cast<EncodeFn>(fn);
    cudaDeviceGetAttribute(&num_sms, cudaDevAttrMultiProcessorCount, 0);
    cudaFuncSetAttribute(fused_kernel, cudaFuncAttributeMaxDynamicSharedMemorySize, SM_TOTAL);
  }
  CUtensorMap tmK, tmV, tmWq, tmWmod, tmWo, tmW1, tmW3, tmW2;
  const CUtensorMapL2promotion P128 = CU_TENSOR_MAP_L2_PROMOTION_L2_128B, P256 = CU_TENSOR_MAP_L2_PROMOTION_L2_256B;
  {
    cuuint64_t dims[2] = {64, (cuuint64_t)NH * SK * 3}, str[1] = {128};
    cuuint32_t box[2] = {64, 192};
    make_map(encode, &tmK, d_in[1], 2, dims, str, box, CU_TENSOR_MAP_SWIZZLE_128B, P256);
    make_map(encode, &tmV, d_in[2], 2, dims, str, box, CU_TENSOR_MAP_SWIZZLE_128B, P256);
  }
  {
    cuuint64_t dims[2] = {NH * DH, D_MODEL}, str[1] = {NH * DH * 2};
    cuuint32_t box[2] = {64, 160};
    make_map(encode, &tmWq, d_in[3], 2, dims, str, box, CU_TENSOR_MAP_SWIZZLE_128B, P128);
  }
  {
    cuuint64_t dims[2] = {6 * D_MODEL, D_MODEL}, str[1] = {6 * D_MODEL * 2};
    cuuint32_t box[2] = {64, 160};
    make_map(encode, &tmWmod, d_in[10], 2, dims, str, box, CU_TENSOR_MAP_SWIZZLE_128B, P128);
  }
  {
    cuuint64_t dims[2] = {D_MODEL, NH * DH}, str[1] = {D_MODEL * 2};
    cuuint32_t box[2] = {64, 192};
    make_map(encode, &tmWo, d_in[4], 2, dims, str, box, CU_TENSOR_MAP_SWIZZLE_128B, P128);
  }
  {
    cuuint64_t dims[3] = {FF, 128, 5}, str[2] = {FF * 2, 128 * FF * 2};
    cuuint32_t box[3] = {16, 128, 5};
    make_map(encode, &tmW1, d_in[6], 3, dims, str, box, CU_TENSOR_MAP_SWIZZLE_32B, P128);
    make_map(encode, &tmW3, d_in[7], 3, dims, str, box, CU_TENSOR_MAP_SWIZZLE_32B, P128);
  }
  {
    cuuint64_t dims[3] = {D_MODEL, 256, 6}, str[2] = {D_MODEL * 2, 256 * D_MODEL * 2};
    cuuint32_t box[3] = {16, 256, 3};
    make_map(encode, &tmW2, d_in[8], 3, dims, str, box, CU_TENSOR_MAP_SWIZZLE_32B, P128);
  }
  Params prm;
  prm.x = (const __nv_bfloat16*)d_in[0];
  prm.c = (const __nv_bfloat16*)d_in[9];
  prm.out = (__nv_bfloat16*)d_out;
  fused_kernel<<<num_sms, NTHREADS, SM_TOTAL, cudaStreamPerThread>>>(tmK, tmV, tmWq, tmWmod, tmWo, tmW1, tmW3, tmW2, prm);
}
```

```cpp
#include <cuda_runtime.h>
#include <cuda_bf16.h>
#include <cuda.h>
#include <stdint.h>

namespace {

constexpr int D_MODEL = 640;
constexpr int NH = 32;
constexpr int SK = 8192;
constexpr int DH = 192;
constexpr int FF = 1536;
constexpr int TPH = 128;
constexpr int NS = 8;
constexpr int SLOT_BYTES = 24576;
constexpr int NCW = 8;
constexpr int W_PROD = NCW, W_JAN = NCW + 1, W_GATH = NCW + 2;
constexpr int NTHREADS = (NCW + 3) * 32;
#define WINDOW 4
#define WIN_HEAD 5
#define WIN_TAIL 2
#define WF_LEAD (NWF * 128 + 128 + N_MS)
#define WIN_FFN 4
#define SHALLOW_LEAD 0
#define TAIL_LEAD 0
#define SLOW_LEAD 128
constexpr int NSTATIC = 5;
#define ORE 4
#define LAG 1
constexpr int QRE = 4;
constexpr int XRE = 4;

constexpr int N_H1 = 80;
constexpr int N_H3 = 96;
constexpr int N_MS = 160;
#define NWF 3
constexpr int N_WO = (NH - NWF) * 10;
constexpr int NK = NH * TPH;
constexpr int NSEQ = NK + NK + N_WO + N_MS;
#define MS_BACK 256
#define N_MSA 40
#define MS_AT (NSEQ - N_MS - MS_BACK)
constexpr int WF_CTA0 = 96;

constexpr int N_F1 = 96;
constexpr int N_F2 = 40;

enum { T_K = 1, T_V = 2, T_WO = 3, T_MS = 4, T_WF = 5, T_END = 15 };

struct __align__(128) Ctr { unsigned v; unsigned pad[31]; };
struct __align__(128) Acc {
  Ctr cntK[NH];
  float2 tstat[NH * TPH];
  float2 hstat[NH];
  float4 o[NH][ORE][DH / 3];
  float2 attn[D_MODEL];
  uint32_t llx1[XRE][D_MODEL / 2];
  uint32_t llhh[FF / 2];
};
struct __align__(128) Par {
  Ctr ticket, hintH3;
  uint32_t llq[QRE][NH * DH / 2];
};
static_assert(sizeof(Acc) % 16 == 0 && sizeof(Par) % 16 == 0, "");

__device__ Acc g_acc;
__device__ Par g_par[2];
__device__ __align__(128) uint2 g_llmod[QRE][3 * D_MODEL];
__device__ unsigned g_epoch;
__device__ volatile unsigned g_sink;
__device__ __align__(128) __nv_bfloat16 g_scores[NH * SK];

#define PROF_STAMP(i) do {} while (0)
#define PROF_SYNC(i) do {} while (0)

constexpr int SM_SLOTS = 0;
constexpr int SM_STAGE = SM_SLOTS + NS * SLOT_BYTES;
constexpr int SM_Q = SM_STAGE + NCW * 768;
constexpr int SM_VA = SM_Q + NH * DH * 2;
constexpr int SM_VH = SM_VA + D_MODEL * 2;
constexpr int SM_X = SM_VH + D_MODEL * 2;
constexpr int SM_RED = SM_X + D_MODEL * 4;
constexpr int SM_BAR = SM_RED + 64 * 8 * 4;
constexpr int SM_DESC = SM_BAR + 40 * 8;
constexpr int SM_TOTAL = SM_DESC + 64;
static_assert(SM_TOTAL <= 232448, "");

struct Params {
  const __nv_bfloat16* x;
  const __nv_bfloat16* c;
  const char* wmod;
  const char* wq;
  const char* kc;
  __nv_bfloat16* out;
};

#define NSLEEP do {} while (0)
__device__ __forceinline__ uint32_t smem_u32(const void* p) { return (uint32_t)__cvta_generic_to_shared(p); }
__device__ __forceinline__ void mbar_init(uint32_t bar, uint32_t cnt) {
  asm volatile("mbarrier.init.shared::cta.b64 [%0], %1;" ::"r"(bar), "r"(cnt) : "memory");
}
__device__ __forceinline__ void mbar_expect_tx(uint32_t bar, uint32_t bytes) {
  asm volatile("mbarrier.arrive.expect_tx.shared::cta.b64 _, [%0], %1;" ::"r"(bar), "r"(bytes) : "memory");
}
__device__ __forceinline__ void mbar_arrive(uint32_t bar) {
  asm volatile("mbarrier.arrive.shared::cta.b64 _, [%0];" ::"r"(bar) : "memory");
}
__device__ __forceinline__ bool mbar_try(uint32_t bar, uint32_t parity) {
  uint32_t ok;
  asm volatile(
      "{\n.reg .pred p;\nmbarrier.try_wait.parity.shared::cta.b64 p, [%1], %2;\nselp.u32 %0, 1, 0, p;\n}"
      : "=r"(ok) : "r"(bar), "r"(parity) : "memory");
  return ok != 0;
}
__device__ __forceinline__ bool mbar_test(uint32_t bar, uint32_t parity) {
  uint32_t ok;
  asm volatile(
      "{\n.reg .pred p;\nmbarrier.test_wait.parity.shared::cta.b64 p, [%1], %2;\nselp.u32 %0, 1, 0, p;\n}"
      : "=r"(ok) : "r"(bar), "r"(parity) : "memory");
  return ok != 0;
}
__device__ __forceinline__ void mbar_wait(uint32_t bar, uint32_t parity) {
  uint32_t it = 0;
  while (!mbar_try(bar, parity)) {
    if (++it > (1u << 24)) __trap();
  }
}
__device__ __forceinline__ void tma_2d(uint32_t dst, const CUtensorMap* tm, int c0, int c1, uint32_t bar, uint64_t pol) {
  asm volatile(
      "cp.async.bulk.tensor.2d.shared::cluster.global.mbarrier::complete_tx::bytes.L2::cache_hint [%0], [%1, {%3, %4}], [%2], %5;"
      ::"r"(dst), "l"(tm), "r"(bar), "r"(c0), "r"(c1), "l"(pol) : "memory");
}
__device__ __forceinline__ void tma_3d(uint32_t dst, const CUtensorMap* tm, int c0, int c1, int c2, uint32_t bar) {
  asm volatile(
      "cp.async.bulk.tensor.3d.shared::cluster.global.mbarrier::complete_tx::bytes [%0], [%1, {%3, %4, %5}], [%2];"
      ::"r"(dst), "l"(tm), "r"(bar), "r"(c0), "r"(c1), "r"(c2) : "memory");
}
__device__ __forceinline__ void prefetch_tm(const CUtensorMap* tm) {
  asm volatile("prefetch.tensormap [%0];" ::"l"(tm) : "memory");
}
__device__ __forceinline__ void ldsm4(uint32_t (&a)[4], uint32_t addr) {
  asm volatile("ldmatrix.sync.aligned.m8n8.x4.shared.b16 {%0,%1,%2,%3}, [%4];"
               : "=r"(a[0]), "=r"(a[1]), "=r"(a[2]), "=r"(a[3]) : "r"(addr) : "memory");
}
__device__ __forceinline__ void ldsm4t(uint32_t (&a)[4], uint32_t addr) {
  asm volatile("ldmatrix.sync.aligned.m8n8.x4.trans.shared.b16 {%0,%1,%2,%3}, [%4];"
               : "=r"(a[0]), "=r"(a[1]), "=r"(a[2]), "=r"(a[3]) : "r"(addr) : "memory");
}
__device__ __forceinline__ void mma16816(float (&d)[4], const uint32_t (&a)[4], uint32_t b0, uint32_t b1) {
  asm volatile(
      "mma.sync.aligned.m16n8k16.row.col.f32.bf16.bf16.f32 {%0,%1,%2,%3}, {%4,%5,%6,%7}, {%8,%9}, {%0,%1,%2,%3};"
      : "+f"(d[0]), "+f"(d[1]), "+f"(d[2]), "+f"(d[3])
      : "r"(a[0]), "r"(a[1]), "r"(a[2]), "r"(a[3]), "r"(b0), "r"(b1));
}
__device__ __forceinline__ unsigned ld_acquire(const unsigned* p) {
  unsigned v;
  asm volatile("ld.acquire.gpu.global.u32 %0, [%1];" : "=r"(v) : "l"(p) : "memory");
  return v;
}
__device__ __forceinline__ unsigned ld_relaxed(const unsigned* p) {
  unsigned v;
  asm volatile("ld.relaxed.gpu.global.u32 %0, [%1];" : "=r"(v) : "l"(p) : "memory");
  return v;
}
__device__ __forceinline__ float2 ld_relaxed_f2(const float* p) {
  float2 v;
  asm volatile("ld.relaxed.gpu.global.v2.f32 {%0,%1}, [%2];" : "=f"(v.x), "=f"(v.y) : "l"(p) : "memory");
  return v;
}
__device__ __forceinline__ float ld_relaxed_f(const float* p) {
  float v;
  asm volatile("ld.relaxed.gpu.global.f32 %0, [%1];" : "=f"(v) : "l"(p) : "memory");
  return v;
}
__device__ __forceinline__ uint2 ld_relaxed_v2(const uint2* p) {
  uint2 v;
  asm volatile("ld.relaxed.gpu.global.v2.u32 {%0,%1}, [%2];" : "=r"(v.x), "=r"(v.y) : "l"(p) : "memory");
  return v;
}
__device__ __forceinline__ uint4 ld_relaxed_v4(const void* p) {
  uint4 v;
  asm volatile("ld.relaxed.gpu.global.v4.u32 {%0,%1,%2,%3}, [%4];" : "=r"(v.x), "=r"(v.y), "=r"(v.z), "=r"(v.w) : "l"(p) : "memory");
  return v;
}
__device__ __forceinline__ void st_relaxed_v2(uint2* p, uint32_t a, uint32_t b) {
  asm volatile("st.relaxed.gpu.global.v2.u32 [%0], {%1, %2};" ::"l"(p), "r"(a), "r"(b) : "memory");
}
__device__ __forceinline__ void st_relaxed(unsigned* p, unsigned v) {
  asm volatile("st.relaxed.gpu.global.u32 [%0], %1;" ::"l"(p), "r"(v) : "memory");
}
__device__ __forceinline__ void fence_gpu() { asm volatile("fence.acq_rel.gpu;" ::: "memory"); }
__device__ __forceinline__ float atom_add_f32(float* p, float v) {
  float r;
  asm volatile("atom.relaxed.gpu.global.add.f32 %0, [%1], %2;" : "=f"(r) : "l"(p), "f"(v) : "memory");
  return r;
}
__device__ __forceinline__ void red_add_v4(float4* p, float a, float b, float c, float d) {
  asm volatile("red.relaxed.gpu.global.add.v4.f32 [%0], {%1, %2, %3, %4};" ::"l"(p), "f"(a), "f"(b), "f"(c), "f"(d) : "memory");
}
__device__ __forceinline__ void red_add_v2(float2* p, float a, float b) {
  asm volatile("red.relaxed.gpu.global.add.v2.f32 [%0], {%1, %2};" ::"l"(p), "f"(a), "f"(b) : "memory");
}
__device__ __forceinline__ float4 ld_relaxed_f4(const float4* p) {
  float4 v;
  asm volatile("ld.relaxed.gpu.global.v4.f32 {%0,%1,%2,%3}, [%4];" : "=f"(v.x), "=f"(v.y), "=f"(v.z), "=f"(v.w) : "l"(p) : "memory");
  return v;
}
__device__ __forceinline__ void red_add_u32(unsigned* p, unsigned v) {
  asm volatile("red.relaxed.gpu.global.add.u32 [%0], %1;" ::"l"(p), "r"(v) : "memory");
}
__device__ __forceinline__ void spin_ge(const unsigned* p, unsigned target) {
  uint32_t it = 0;
  while (ld_relaxed(p) < target) {
    if (++it > (1u << 22)) __trap();
  }
}
__device__ __forceinline__ void spin_ge_sleep(const unsigned* p, unsigned target) {
  uint32_t it = 0;
  while (ld_relaxed(p) < target) {
    NSLEEP;
    if (++it > (1u << 22)) __trap();
  }
}
__device__ __forceinline__ void cons_bar() { asm volatile("bar.sync 1, 256;" ::: "memory"); }

__device__ __forceinline__ uint32_t pack_bf16(float lo, float hi) {
  uint32_t r;
  asm("cvt.rn.bf16x2.f32 %0, %1, %2;" : "=r"(r) : "f"(hi), "f"(lo));
  return r;
}
__device__ __forceinline__ float bf16r(float x) { return __uint_as_float(pack_bf16(0.f, x) & 0xffff0000u); }
__device__ __forceinline__ float bf_lo(uint32_t v) { return __uint_as_float(v << 16); }
__device__ __forceinline__ float bf_hi(uint32_t v) { return __uint_as_float(v & 0xffff0000u); }
__device__ __forceinline__ float warp_sum(float v) {
#pragma unroll
  for (int o = 16; o > 0; o >>= 1) v += __shfl_xor_sync(0xffffffffu, v, o);
  return v;
}
__device__ __forceinline__ float warp_max(float v) {
#pragma unroll
  for (int o = 16; o > 0; o >>= 1) v = fmaxf(v, __shfl_xor_sync(0xffffffffu, v, o));
  return v;
}
__device__ __forceinline__ float fast_exp(float x) {
  float r;
  asm("ex2.approx.ftz.f32 %0, %1;" : "=f"(r) : "f"(x * 1.4426950408889634f));
  return r;
}
__device__ __forceinline__ float silu_f(float x) {
  float r;
  asm("rcp.approx.f32 %0, %1;" : "=f"(r) : "f"(1.0f + fast_exp(-x)));
  return x * r;
}
__device__ __forceinline__ float sel4(int j, float a, float b, float c, float d) {
  float lo = (j & 1) ? b : a, hi = (j & 1) ? d : c;
  return (j & 2) ? hi : lo;
}

__device__ __forceinline__ void signal_after(unsigned* ctr, uint32_t dep, int lane) {
  const unsigned any = __ballot_sync(0xffffffffu, dep == 0x7fc5a5a5u);
  if (any) g_sink = any;
  if (lane == 0) red_add_u32(ctr, 1u);
}

template <int KS>
__device__ __forceinline__ void gemv_tile(uint32_t slot, const uint32_t* vec32, int lane, float& v0, float& v1) {
  const int j = lane & 3;
  const int r0 = (lane & 7) + ((lane >> 4) << 3), lo = (lane >> 3) & 1;
  const uint32_t vg = slot + r0 * 128 + ((lo ^ (r0 & 7)) << 4);
  float acc[3][4][4];
#pragma unroll
  for (int c = 0; c < 3; c++)
#pragma unroll
    for (int m = 0; m < 4; m++) { acc[c][m][0] = acc[c][m][1] = acc[c][m][2] = acc[c][m][3] = 0.f; }
#pragma unroll
  for (int ks = 0; ks < KS; ks++) {
    const uint32_t b0 = vec32[8 * ks + j], b1 = vec32[8 * ks + 4 + j];
#pragma unroll
    for (int m = 0; m < 4; m++) {
      uint32_t a[4];
      ldsm4t(a, (vg + ks * 2048) ^ (m << 5));
      mma16816(acc[ks % 3][m], a, b0, b1);
    }
  }
  float r0v[4], r2v[4];
#pragma unroll
  for (int m = 0; m < 4; m++) {
    r0v[m] = acc[0][m][0] + acc[1][m][0] + acc[2][m][0];
    r2v[m] = acc[0][m][2] + acc[1][m][2] + acc[2][m][2];
  }
  v0 = sel4(j, r0v[0], r0v[1], r0v[2], r0v[3]);
  v1 = sel4(j, r2v[0], r2v[1], r2v[2], r2v[3]);
}

__device__ __forceinline__ void slice_frags(uint32_t slot, int warp, int lane, uint32_t (&af)[5][4]) {
  const int r0 = (lane & 7) + ((lane >> 4) << 3), lo = (lane >> 3) & 1;
  const uint32_t w = slot + (warp * 80 + r0) * 32 + ((lo ^ ((r0 >> 2) & 1)) << 4);
#pragma unroll
  for (int ks = 0; ks < 5; ks++) ldsm4t(af[ks], w + ks * 512);
}
__device__ __forceinline__ void slice_mma(const uint32_t (&af)[5][4], const uint32_t (&b)[10], float* red, int warp, int lane) {
  float a[3][4];
#pragma unroll
  for (int i = 0; i < 3; i++) { a[i][0] = a[i][1] = a[i][2] = a[i][3] = 0.f; }
#pragma unroll
  for (int ks = 0; ks < 5; ks++) mma16816(a[ks % 3], af[ks], b[2 * ks], b[2 * ks + 1]);
  if ((lane & 3) == 0) {
    red[(lane >> 2) * 8 + warp] = a[0][0] + a[1][0] + a[2][0];
    red[(8 + (lane >> 2)) * 8 + warp] = a[0][2] + a[1][2] + a[2][2];
  }
}
__device__ __forceinline__ void vec_frags(const uint32_t* vec32, int warp, int lane, uint32_t (&b)[10]) {
#pragma unroll
  for (int ks = 0; ks < 5; ks++) {
    b[2 * ks] = vec32[40 * warp + 8 * ks + (lane & 3)];
    b[2 * ks + 1] = vec32[40 * warp + 8 * ks + 4 + (lane & 3)];
  }
}
__device__ __forceinline__ float red8(const float* red, int col) {
  const float4 a = *reinterpret_cast<const float4*>(red + col * 8), b = *reinterpret_cast<const float4*>(red + col * 8 + 4);
  return ((a.x + a.y) + (a.z + a.w)) + ((b.x + b.y) + (b.z + b.w));
}

__device__ __forceinline__ void ln_stats(const float* xs, int lane, float& mean_b, float& rstd) {
  const float k0 = xs[0];
  float s1[4] = {0.f, 0.f, 0.f, 0.f}, s2[4] = {0.f, 0.f, 0.f, 0.f};
#pragma unroll
  for (int i = 0; i < 5; i++) {
    const float4 v = reinterpret_cast<const float4*>(xs)[lane + 32 * i];
    const float d0 = v.x - k0, d1 = v.y - k0, d2 = v.z - k0, d3 = v.w - k0;
    s1[0] += d0; s1[1] += d1; s1[2] += d2; s1[3] += d3;
    s2[0] = fmaf(d0, d0, s2[0]); s2[1] = fmaf(d1, d1, s2[1]); s2[2] = fmaf(d2, d2, s2[2]); s2[3] = fmaf(d3, d3, s2[3]);
  }
  float a = (s1[0] + s1[1]) + (s1[2] + s1[3]), b = (s2[0] + s2[1]) + (s2[2] + s2[3]);
#pragma unroll
  for (int o = 16; o > 0; o >>= 1) {
    a += __shfl_xor_sync(0xffffffffu, a, o);
    b += __shfl_xor_sync(0xffffffffu, b, o);
  }
  const float md = a * (1.0f / D_MODEL);
  const float var = fmaxf(fmaf(-md, md, b * (1.0f / D_MODEL)), 0.f);
  mean_b = bf16r(k0 + md);
  float sd;
  asm("sqrt.approx.ftz.f32 %0, %1;" : "=f"(sd) : "f"(bf16r(bf16r(var) + 1e-5f)));
  asm("rcp.approx.ftz.f32 %0, %1;" : "=f"(rstd) : "f"(bf16r(sd)));
}
__device__ __forceinline__ uint32_t ln_mod2(float x0, float x1, float mean_b, float rstd, uint32_t cpair, uint32_t spair) {
  const uint32_t c1 = pack_bf16(1.0f + bf_lo(cpair), 1.0f + bf_hi(cpair));
  const uint32_t a = pack_bf16(x0 - mean_b, x1 - mean_b);
  const uint32_t n = pack_bf16(bf_lo(a) * rstd, bf_hi(a) * rstd);
  const uint32_t t = pack_bf16(bf_lo(n) * bf_lo(c1), bf_hi(n) * bf_hi(c1));
  return pack_bf16(bf_lo(t) + bf_lo(spair), bf_hi(t) + bf_hi(spair));
}

__global__ void __launch_bounds__(NTHREADS, 1)
fused_kernel(const __grid_constant__ CUtensorMap tmK, const __grid_constant__ CUtensorMap tmV,
             const __grid_constant__ CUtensorMap tmWq,
             const __grid_constant__ CUtensorMap tmWmodS,
             const __grid_constant__ CUtensorMap tmWo, const __grid_constant__ CUtensorMap tmW1,
             const __grid_constant__ CUtensorMap tmW3, const __grid_constant__ CUtensorMap tmW2,
             const Params prm) {
  extern __shared__ __align__(1024) unsigned char smem[];
  const uint32_t sb = smem_u32(smem);
  const int tid = threadIdx.x, warp = tid >> 5, lane = tid & 31;
  const int cta = blockIdx.x, G = gridDim.x;
  const uint32_t bar_full = sb + SM_BAR, bar_empty = bar_full + NS * 16, bar_post = bar_empty + NS * 8,
                 bar_tail = bar_post + NS * 8, bar_clear = bar_tail + 32, bar_mod = bar_clear + 8, bar_q = bar_mod + 8,
                 bar_wf = bar_q + 8;
  volatile uint32_t* desc = reinterpret_cast<volatile uint32_t*>(smem + SM_DESC);
  volatile uint32_t* tailslot = desc + 8;
  volatile uint32_t* s_epoch = desc + 12;
  Acc* const acc = &g_acc;
  const int h1 = cta - (G - N_H1);
  const int has_h1 = h1 >= 0 ? 1 : 0;
  const bool has_h3 = cta < N_H3;
  const int nh = has_h1 + (has_h3 ? 4 : 0);
  const bool has_f1 = cta < N_F1;
  const int f2 = G - 1 - cta;
  const bool has_f2 = cta >= N_F1 && f2 < N_F2;
  const int f2b = f2 + (G - N_F1);
  const bool has_f2b = has_f2 && f2b < N_F2;
  const int wf = cta - WF_CTA0;
  const bool has_wf = wf >= 0 && wf < 10;

  if (warp == W_PROD) {
    if (lane == 0) {
      PROF_SYNC(0);
      for (int i = 0; i < NS; i++) {
        mbar_init(bar_full + 16 * i, 1); mbar_init(bar_full + 16 * i + 8, 1);
        mbar_init(bar_empty + 8 * i, 1); mbar_init(bar_post + 8 * i, 1);
      }
      for (int i = 0; i < 7; i++) mbar_init(bar_tail + 8 * i, 1);
      mbar_init(bar_wf, NWF - 1);
      asm volatile("fence.mbarrier_init.release.cluster;" ::: "memory");
      asm volatile("fence.proxy.async.shared::cta;" ::: "memory");
      if (has_h1) {
        mbar_expect_tx(bar_full, D_MODEL * 32);
        tma_3d(sb, &tmWmodS, h1 * 16, 0, 0, bar_full);
        mbar_arrive(bar_full + 8);
      }
      prefetch_tm(&tmWq);
      for (int i = 0; i < nh; i++) mbar_arrive(bar_post + 8 * i);
      prefetch_tm(&tmK);
      prefetch_tm(&tmV);
      prefetch_tm(&tmWo);
    }
    __syncwarp();
    asm volatile("bar.arrive 3, 64;" ::: "memory");
  } else if (warp == W_JAN) {
    uint4* z = reinterpret_cast<uint4*>(acc);
    constexpr int NZ = sizeof(Acc) / 16;
    const int per = (NZ + G - 1) / G;
    for (int i = cta * per + lane; i < min(NZ, (cta + 1) * per); i += 32) z[i] = make_uint4(0, 0, 0, 0);
    __syncwarp();
    if (lane == 0) fence_gpu();
    const unsigned e = *reinterpret_cast<volatile unsigned*>(&g_epoch);
    asm volatile("bar.sync 3, 64;" ::: "memory");
    if (lane == 0) { mbar_arrive(bar_clear); PROF_STAMP(4); }
    uint4* nx = reinterpret_cast<uint4*>(&g_par[(e & 1) ^ 1]);
    constexpr int NZP = sizeof(Par) / 16;
    for (int i = cta * 32 + lane; i < NZP; i += G * 32) nx[i] = make_uint4(0, 0, 0, 0);
    return;
  } else if (warp == W_GATH) {
    {
      const char* pa = lane < 3 ? prm.wmod + min(lane * (2 << 20) + h1 * 32 * (h1 >= 0), 6 * D_MODEL * D_MODEL * 2 - 128)
                     : lane < 7 ? prm.wq + min((lane - 3) * (2 << 20), NH * DH * D_MODEL * 2 - 128)
                                : prm.kc + (size_t)(lane - 7) * (2 << 20) + (size_t)(cta & 63) * SLOT_BYTES;
      if (lane < 16) asm volatile("prefetch.global.L2 [%0];" ::"l"(pa));
    }
    const uint4* src = reinterpret_cast<const uint4*>(g_llmod[cta & (QRE - 1)]) + lane;
    uint4 v[10];
#pragma unroll
    for (int i = 0; i < 10; i++) v[i] = ld_relaxed_v4(src + i * 32);
    const unsigned e = *reinterpret_cast<volatile unsigned*>(&g_epoch);
    if (lane == 0) *s_epoch = e;
    __syncwarp();
    asm volatile("bar.sync 0, %0;" ::"n"(NTHREADS - 32) : "memory");
    const unsigned tg = e + 1;
    uint32_t pend = 0x3ff, it = 0;
    for (;;) {
#pragma unroll
      for (int i = 0; i < 10; i++)
        if (((pend >> i) & 1u) && v[i].y == tg && v[i].w == tg) {
          reinterpret_cast<uint2*>(smem + SM_Q)[i * 32 + lane] = make_uint2(v[i].x, v[i].z);
          pend &= ~(1u << i);
        }
      if (!pend) break;
      NSLEEP;
#pragma unroll
      for (int i = 0; i < 10; i++)
        if ((pend >> i) & 1u) v[i] = ld_relaxed_v4(src + i * 32);
      if (++it > (1u << 22)) __trap();
    }
    __syncwarp();
    if (lane == 0) {
      PROF_STAMP(36);
      mbar_arrive(bar_mod);
      const unsigned* hint = &g_par[e & 1].hintH3.v;
      uint32_t it2 = 0;
      while (ld_acquire(hint) < (unsigned)G) {
        NSLEEP;
        if (++it2 > (1u << 22)) __trap();
      }
      PROF_STAMP(37);
      mbar_arrive(bar_q);
    }
    return;
  } else {
    uint32_t* va = reinterpret_cast<uint32_t*>(smem + SM_VA);
    float* xs = reinterpret_cast<float*>(smem + SM_X);
    const int p1 = tid + 256;
    const uint32_t cv0 = __ldg(reinterpret_cast<const uint32_t*>(prm.c) + tid);
    const uint32_t xv0 = __ldg(reinterpret_cast<const uint32_t*>(prm.x) + tid);
    uint32_t cv1 = 0, xv1 = 0;
    if (tid < 64) {
      cv1 = __ldg(reinterpret_cast<const uint32_t*>(prm.c) + p1);
      xv1 = __ldg(reinterpret_cast<const uint32_t*>(prm.x) + p1);
    }
    va[tid] = pack_bf16(silu_f(bf_lo(cv0)), silu_f(bf_hi(cv0)));
    xs[2 * tid] = bf_lo(xv0);
    xs[2 * tid + 1] = bf_hi(xv0);
    if (tid < 64) {
      va[p1] = pack_bf16(silu_f(bf_lo(cv1)), silu_f(bf_hi(cv1)));
      xs[2 * p1] = bf_lo(xv1);
      xs[2 * p1 + 1] = bf_hi(xv1);
    }
  }
  asm volatile("bar.sync 0, %0;" ::"n"(NTHREADS - 32) : "memory");
  const unsigned ep = *s_epoch;
  Par* const par = &g_par[ep & 1];

  if (warp == W_PROD) {
    if (lane != 0) return;
    uint64_t pol;
    asm volatile("createpolicy.fractional.L2::evict_first.b64 %0, 1.0;" : "=l"(pol));
    uint32_t tkA = atomicAdd(&par->ticket.v, 1u);
    uint32_t tkB = atomicAdd(&par->ticket.v, 1u);
    int win = WIN_HEAD;
    bool head_phase = true;
    unsigned long long fifo = 0;
    int nfifo = 0;
    auto throttle = [&]() {
      if (nfifo >= win) {
        const uint32_t e = (uint32_t)(fifo >> (7 * (win - 1))) & 127u;
        mbar_wait(bar_full + 8 * (e >> 1), e & 1u);
      }
    };
    auto push = [&](uint32_t idx, uint32_t parity) { fifo = (fifo << 7) | (idx << 1) | parity; nfifo++; };
    uint32_t active = (1u << NS) - 1, used = 0, upar = 0;
    int cur = 0;
    auto acquire = [&]() {
      const int s = cur;
      do { cur = (cur + 1) & (NS - 1); } while (!((active >> cur) & 1u));
      if ((used >> s) & 1u) mbar_wait(bar_empty + 8 * s, ((upar >> s) & 1u) ^ 1u);
      return s;
    };
    auto post = [&](int s, uint32_t d) {
      desc[s] = d;
      mbar_arrive(bar_post + 8 * s);
    };
    auto issue_half = [&](int s, int h, const CUtensorMap* tm, int c0, int c1, uint32_t bytes, uint32_t dst) {
      throttle();
      const uint32_t bar = bar_full + 16 * s + 8 * h;
      mbar_expect_tx(bar, bytes);
      tma_2d(dst, tm, c0, c1, bar, pol);
      push(2 * s + h, (upar >> s) & 1u);
    };
    auto done_slot = [&](int s) { upar ^= 1u << s; used |= 1u << s; };
    if (has_h1) { acquire(); push(0, 0); push(0, 0); done_slot(0); }
    for (int i = has_h1; i < nh; i++) {
      const int s = acquire();
      issue_half(s, 0, &tmWq, cta * 64, (i - has_h1) * 160, 80 * 128, sb + s * SLOT_BYTES);
      issue_half(s, 1, &tmWq, cta * 64, (i - has_h1) * 160 + 80, 80 * 128, sb + s * SLOT_BYTES + 80 * 128);
      done_slot(s);
    }
    int istat = 0;
    int wf_left = has_wf ? NWF : 0;
    bool tail_done = false, shallow = false;
    for (;;) {
      uint32_t seq;
      if (istat < 0) {
        seq = NSEQ;
      } else if (istat < NSTATIC) {
        seq = cta + G * istat;
        istat++;
      } else {
        if (tkA == 0xfffffffeu) tkA = atomicAdd(&par->ticket.v, 1u);
        seq = tkA == 0xffffffffu ? NSEQ : NSTATIC * G + tkA;
        tkA = tkB;
        if (seq < NSEQ) {
          if (has_wf && seq >= NSEQ - WF_LEAD) {
            tkB = 0xffffffffu;
          } else if (!shallow && seq >= NSEQ - SHALLOW_LEAD) {
            shallow = true;
            tkB = 0xfffffffeu;
          } else if (shallow) {
            tkA = atomicAdd(&par->ticket.v, 1u);
          } else {
            tkB = atomicAdd(&par->ticket.v, 1u);
          }
        }
      }
      if (!tail_done && seq >= NSEQ - TAIL_LEAD && (seq < NSEQ || wf_left == 0)) {
        tail_done = true;
        win = WIN_FFN;
        const int nt = has_f1 ? 2 : has_f2b ? 4 : has_f2 ? 2 : 0;
        for (int k = 0; k < nt; k++) {
          const int ti = has_f1 ? k : (k + 2) & 3;
          const int s = acquire();
          active &= ~(1u << s);
          post(s, (uint32_t)T_END << 28);
          throttle();
          const uint32_t dst = sb + s * SLOT_BYTES, bar = bar_tail + 8 * ti;
          tailslot[ti] = s;
          if (has_f1) {
            mbar_expect_tx(bar, D_MODEL * 32);
            tma_3d(dst, ti == 0 ? &tmW1 : &tmW3, cta * 16, 0, 0, bar);
          } else {
            mbar_expect_tx(bar, 768 * 32);
            tma_3d(dst, &tmW2, (ti >= 2 ? f2 : f2b) * 16, 0, (ti & 1) * 3, bar);
          }
          push(32 + ti, 0); push(32 + ti, 0);
        }
      }
      int type, a, b;
      if (seq >= NSEQ) {
        if (wf_left == 0) break;
        type = T_WF; a = NH - wf_left; b = wf;
        wf_left--;
        istat = -1;
      } else if (seq >= MS_AT && seq < MS_AT + N_MSA) {
        type = T_MS; a = 0; b = N_H1 + (seq - MS_AT);
      } else if (seq >= NSEQ - (N_MS - N_MSA)) {
        type = T_MS; a = 0; b = N_H1 + N_MS - (NSEQ - seq);
      } else if (seq < NK + (MS_AT < NK ? N_MSA : 0)) {
        const uint32_t k = seq < MS_AT ? seq : seq - N_MSA;
        type = T_K; a = k >> 7; b = k & 127;
      } else {
        uint32_t r = seq - NK - (seq >= MS_AT ? N_MSA : 0);
        if (r < LAG * TPH) {
          type = T_V; a = r >> 7; b = r & 127;
        } else {
          r -= LAG * TPH;
          constexpr uint32_t NBLK = NH - NWF;
          const uint32_t blk = r / 138u, off = r - blk * 138u;
          if (blk < NBLK) {
            if (off < TPH) { type = T_V; a = LAG + blk; b = off; }
            else { type = T_WO; a = blk; b = off - TPH; }
          } else {
            r -= NBLK * 138u;
            type = T_V; a = LAG + NBLK + (r >> 7); b = r & 127;
          }
        }
      }
      const int s = acquire();
      post(s, ((uint32_t)type << 28) | (a << 16) | b);
      if (head_phase && mbar_test(bar_q, 0)) { head_phase = false; win = WINDOW; }
      if (seq >= NSEQ - (N_MS - N_MSA) - SLOW_LEAD && type != T_WF && !tail_done) win = WIN_TAIL;
      const uint32_t dst = sb + s * SLOT_BYTES;
      if (type == T_MS) {
        throttle();
        mbar_expect_tx(bar_full + 16 * s, D_MODEL * 32);
        tma_3d(dst, &tmWmodS, b * 16, 0, 0, bar_full + 16 * s);
        mbar_arrive(bar_full + 16 * s + 8);
        push(2 * s, (upar >> s) & 1u); push(2 * s, (upar >> s) & 1u);
      } else {
        const CUtensorMap* tm = type == T_K ? &tmK : type == T_V ? &tmV : &tmWo;
        const int c0 = (type == T_K || type == T_V) ? 0 : b * 64;
        const int c1 = (type == T_K || type == T_V) ? (a * TPH + b) * 192 : a * DH;
        issue_half(s, 0, tm, c0, c1, 96 * 128, dst);
        issue_half(s, 1, tm, c0, c1 + 96, 96 * 128, dst + 96 * 128);
      }
      done_slot(s);
    }
    PROF_STAMP(8);
    uint32_t pending = active;
    uint32_t it = 0;
    while (pending) {
      for (int s = 0; s < NS; s++) {
        if (!((pending >> s) & 1u)) continue;
        if (((used >> s) & 1u) && !mbar_test(bar_empty + 8 * s, ((upar >> s) & 1u) ^ 1u)) continue;
        pending &= ~(1u << s);
        post(s, (uint32_t)T_END << 28);
      }
      if (++it > (1u << 24)) __trap();
    }
    return;
  }

  const int g = lane >> 2, j = lane & 3;
  float* xs = reinterpret_cast<float*>(smem + SM_X);
  float* red = reinterpret_cast<float*>(smem + SM_RED);
  uint32_t* vh = reinterpret_cast<uint32_t*>(smem + SM_VH);

  {
    uint32_t bf[10];
    if (has_h1) {
      uint32_t af[5][4];
      vec_frags(reinterpret_cast<const uint32_t*>(smem + SM_VA), warp, lane, bf);
      mbar_wait(bar_full, 0);
      if (tid == 0) PROF_STAMP(38);
      slice_frags(sb, warp, lane, af);
      slice_mma(af, bf, red, warp, lane);
      cons_bar();
      if (warp == 0) {
        const float v = red8(red, lane & 15);
        const float vn = __shfl_down_sync(0xffffffffu, v, 1);
        if (!(lane & 1)) {
          const uint32_t w = pack_bf16(v, vn);
          st_relaxed_v2(&g_llmod[(lane >> 4) * 2][h1 * 8 + ((lane & 15) >> 1)], w, ep + 1);
          st_relaxed_v2(&g_llmod[(lane >> 4) * 2 + 1][h1 * 8 + ((lane & 15) >> 1)], w, ep + 1);
        }
        if (lane == 0) { mbar_arrive(bar_empty); PROF_STAMP(7); }
        __syncwarp();
      }
    }
    float mean_b, rstd;
    ln_stats(xs, lane, mean_b, rstd);
    const uint32_t* sc = reinterpret_cast<const uint32_t*>(smem + SM_Q);
    mbar_wait(bar_mod, 0);
    for (int p = tid; p < D_MODEL / 2; p += 256) vh[p] = ln_mod2(xs[2 * p], xs[2 * p + 1], mean_b, rstd, sc[320 + p], sc[p]);
    __syncwarp();
    cons_bar();
    if (tid == 0) PROF_STAMP(29);
    if (has_h3) {
      vec_frags(vh, warp, lane, bf);
      const int sl = has_h1 + (warp >> 1);
      mbar_wait(bar_full + 16 * sl + 8 * (warp & 1), 0);
      if (tid == 0) PROF_STAMP(48);
      const int r0 = (lane & 7) + ((lane >> 4) << 3), lo = (lane >> 3) & 1;
      const uint32_t vg = sb + sl * SLOT_BYTES + ((warp & 1) * 80 + r0) * 128 + ((lo ^ (r0 & 7)) << 4);
      float qa[4][4];
#pragma unroll
      for (int m = 0; m < 4; m++) { qa[m][0] = qa[m][1] = qa[m][2] = qa[m][3] = 0.f; }
#pragma unroll
      for (int ks = 0; ks < 5; ks++) {
#pragma unroll
        for (int m = 0; m < 4; m++) {
          uint32_t a4[4];
          ldsm4t(a4, (vg + ks * 2048) ^ (m << 5));
          mma16816(qa[m], a4, bf[2 * ks], bf[2 * ks + 1]);
        }
      }
      red[(16 * j + g) * 8 + warp] = sel4(j, qa[0][0], qa[1][0], qa[2][0], qa[3][0]);
      red[(16 * j + 8 + g) * 8 + warp] = sel4(j, qa[0][2], qa[1][2], qa[2][2], qa[3][2]);
      cons_bar();
      if (tid < 64) {
        mbar_wait(bar_clear, 0);
        const float v = red8(red, tid);
        const float vn = __shfl_down_sync(0xffffffffu, v, 1);
        if (!(tid & 1)) {
          const uint32_t w = ~pack_bf16(v, vn);
#pragma unroll
          for (int r = 0; r < QRE; r++) st_relaxed(&par->llq[r][cta * 32 + (tid >> 1)], w);
        }
        if (tid < 4) mbar_arrive(bar_empty + 8 * (has_h1 + tid));
        __syncwarp();
        if (tid == 32) red_add_u32(&par->hintH3.v, 1u);
      }
    } else if (tid == 0) {
      mbar_wait(bar_clear, 0);
      red_add_u32(&par->hintH3.v, 1u);
    }
    if (tid == 0) PROF_STAMP(2);
    mbar_wait(bar_q, 0);
    {
      uint32_t pend = 7, it = 0;
      while (pend) {
        uint4 v[3];
#pragma unroll
        for (int i = 0; i < 3; i++)
          if ((pend >> i) & 1u) v[i] = ld_relaxed_v4(reinterpret_cast<const uint4*>(par->llq[cta & (QRE - 1)]) + i * 256 + tid);
#pragma unroll
        for (int i = 0; i < 3; i++)
          if (((pend >> i) & 1u) && v[i].x != 0u && v[i].y != 0u && v[i].z != 0u && v[i].w != 0u) {
            reinterpret_cast<uint4*>(smem + SM_Q)[i * 256 + tid] = make_uint4(~v[i].x, ~v[i].y, ~v[i].z, ~v[i].w);
            pend &= ~(1u << i);
          }
        if (pend) NSLEEP;
        if (++it > (1u << 22)) __trap();
      }
    }
    __syncwarp();
    cons_bar();
    if (tid == 0) {
      if (cta == 0) g_epoch = ep + 1;
      PROF_STAMP(3);
    }
  }

  {
    const uint32_t slot = sb + warp * SLOT_BYTES;
    const uint32_t my_full = bar_full + 16 * warp, my_empty = bar_empty + 8 * warp, my_post = bar_post + 8 * warp;
    uint32_t* stage = reinterpret_cast<uint32_t*>(smem + SM_STAGE + warp * 768);
    uint32_t vk[3], vv[3];
    {
      const int r0 = (lane & 7) + (((lane >> 3) & 1) << 3), hi = lane >> 4;
      const int r1 = (lane & 7) + ((lane >> 4) << 3), lo = (lane >> 3) & 1;
#pragma unroll
      for (int t = 0; t < 3; t++) {
        vk[t] = slot + (3 * r0 + t) * 128 + ((hi ^ ((3 * r0 + t) & 7)) << 4);
        vv[t] = slot + (3 * r1 + t) * 128 + ((lo ^ ((3 * r1 + t) & 7)) << 4);
      }
    }
    uint32_t use = (warp < nh) ? 1 : 0;
    for (;; use++) {
      mbar_wait(my_post, use & 1);
      const uint32_t d = desc[warp];
      const int type = d >> 28, a = (d >> 16) & 0xfff, b = d & 0xffff;
      if (type == T_K) {
        const uint32_t* q32 = reinterpret_cast<const uint32_t*>(smem + SM_Q) + a * (DH / 2);
        float s[4][4];
#pragma unroll
        for (int m = 0; m < 4; m++) { s[m][0] = s[m][1] = s[m][2] = s[m][3] = 0.f; }
        mbar_wait(my_full, use & 1);
        mbar_wait(my_full + 8, use & 1);
#pragma unroll
        for (int ks = 0; ks < 12; ks++) {
          const uint32_t b0 = q32[8 * ks + j], b1 = q32[8 * ks + 4 + j];
#pragma unroll
          for (int m = 0; m < 4; m++) {
            uint32_t af[4];
            ldsm4(af, (vk[ks >> 2] ^ ((ks & 3) << 5)) + m * 6144);
            mma16816(s[m], af, b0, b1);
          }
        }
        __syncwarp();
        if (lane == 0) mbar_arrive(my_empty);
        const float scale = 0.07216878364870323f;
        const float s0 = bf16r(sel4(j, s[0][0], s[1][0], s[2][0], s[3][0])) * scale;
        const float s1 = bf16r(sel4(j, s[0][2], s[1][2], s[2][2], s[3][2])) * scale;
        __nv_bfloat16* st16 = reinterpret_cast<__nv_bfloat16*>(stage);
        st16[16 * j + g] = __float2bfloat16_rn(s0);
        st16[16 * j + 8 + g] = __float2bfloat16_rn(s1);
        __syncwarp();
        const uint32_t pr = stage[lane];
        reinterpret_cast<uint32_t*>(g_scores)[a * (SK / 2) + b * 32 + lane] = pr;
        const float e0 = bf_lo(pr), e1 = bf_hi(pr);
        const float tmax = warp_max(fmaxf(e0, e1));
        const float tsum = warp_sum(fast_exp(e0 - tmax) + fast_exp(e1 - tmax));
        unsigned old = 0;
        if (lane == 0) acc->tstat[a * TPH + b] = make_float2(tmax, tsum);
        __syncwarp();
        if (lane == 0) {
          fence_gpu();
          old = atomicAdd(&acc->cntK[a].v, 1u);
        }
        old = __shfl_sync(0xffffffffu, old, 0);
        if (old == TPH - 1) {
          fence_gpu();
          const float4 t0 = __ldcg(reinterpret_cast<const float4*>(acc->tstat + a * TPH) + lane);
          const float4 t1 = __ldcg(reinterpret_cast<const float4*>(acc->tstat + a * TPH) + 32 + lane);
          const float m = warp_max(fmaxf(fmaxf(t0.x, t0.z), fmaxf(t1.x, t1.z)));
          const float l = warp_sum(t0.y * fast_exp(t0.x - m) + t0.w * fast_exp(t0.z - m) +
                                   t1.y * fast_exp(t1.x - m) + t1.w * fast_exp(t1.z - m));
          if (lane == 0) {
            fence_gpu();
            asm volatile("st.relaxed.gpu.global.v2.f32 [%0], {%1, %2};" ::"l"(&acc->hstat[a]), "f"(m), "f"(1.0f / l) : "memory");
          }
        }
      } else if (type == T_V) {
        {
          float2 hs;
          uint32_t it = 0;
          do {
            asm volatile("ld.relaxed.gpu.global.v2.f32 {%0, %1}, [%2];" : "=f"(hs.x), "=f"(hs.y) : "l"(&acc->hstat[a]) : "memory");
            if (++it > (1u << 22)) __trap();
          } while (hs.y == 0.f);
          const uint32_t pr = __ldcg(reinterpret_cast<const uint32_t*>(g_scores) + a * (SK / 2) + b * 32 + lane);
          stage[lane] = pack_bf16(fast_exp(bf_lo(pr) - hs.x) * hs.y, fast_exp(bf_hi(pr) - hs.x) * hs.y);
        }
        __syncwarp();
        uint32_t pb[8];
#pragma unroll
        for (int i = 0; i < 8; i++) pb[i] = stage[4 * i + j];
        float o[12][4];
#pragma unroll
        for (int m = 0; m < 12; m++) { o[m][0] = o[m][1] = o[m][2] = o[m][3] = 0.f; }
        mbar_wait(my_full, use & 1);
        mbar_wait(my_full + 8, use & 1);
#pragma unroll
        for (int ks = 0; ks < 4; ks++) {
#pragma unroll
          for (int m = 0; m < 12; m++) {
            uint32_t af[4];
            ldsm4t(af, (vv[m >> 2] ^ ((m & 3) << 5)) + ks * 6144);
            mma16816(o[m], af, pb[2 * ks], pb[2 * ks + 1]);
          }
        }
        __syncwarp();
        if (lane == 0) mbar_arrive(my_empty);
        {
          float* sf = reinterpret_cast<float*>(stage);
#pragma unroll
          for (int i = 0; i < 3; i++) {
            sf[16 * (4 * i + j) + g] = sel4(j, o[4 * i][0], o[4 * i + 1][0], o[4 * i + 2][0], o[4 * i + 3][0]);
            sf[16 * (4 * i + j) + 8 + g] = sel4(j, o[4 * i][2], o[4 * i + 1][2], o[4 * i + 2][2], o[4 * i + 3][2]);
          }
          __syncwarp();
          float4* dst = acc->o[a][cta & (ORE - 1)];
          red_add_v4(dst + lane, sf[3 * lane], sf[3 * lane + 1], sf[3 * lane + 2], 1.0f);
          red_add_v4(dst + 32 + lane, sf[96 + 3 * lane], sf[96 + 3 * lane + 1], sf[96 + 3 * lane + 2], 1.0f);
          __syncwarp();
        }
      } else if (type == T_WO || type == T_WF) {
        const int c0 = b * 64 + 16 * j + g;
        const bool last = type == T_WF && a == NH - 1;
        float pre0 = 0.f, pre1 = 0.f;
        uint2 gw0 = make_uint2(0u, 0u), gw1 = make_uint2(0u, 0u);
        if (last) {
          const uint2* gp = &g_llmod[cta & (QRE - 1)][2 * (D_MODEL / 2)];
          uint32_t itg = 0;
          do {
            gw0 = ld_relaxed_v2(gp + (c0 >> 1)); gw1 = ld_relaxed_v2(gp + ((c0 + 8) >> 1));
            if (++itg > (1u << 22)) __trap();
          } while (gw0.y != ep + 1 || gw1.y != ep + 1);
          __syncwarp();
          {
            float2 t0, t1;
            uint32_t it = 0;
            do {
              t0 = ld_relaxed_f2(reinterpret_cast<const float*>(acc->attn + c0));
              t1 = ld_relaxed_f2(reinterpret_cast<const float*>(acc->attn + c0 + 8));
              if (++it > (1u << 22)) __trap();
            } while (t0.y != (float)(NH - NWF) || t1.y != (float)(NH - NWF));
            pre0 = t0.x; pre1 = t1.x;
          }
          __syncwarp();
        }
        {
          float4 u0, u1;
          uint32_t it = 0;
          for (;;) {
            float4 t[2][ORE];
#pragma unroll
            for (int r = 0; r < ORE; r++) { t[0][r] = ld_relaxed_f4(&acc->o[a][r][lane]); t[1][r] = ld_relaxed_f4(&acc->o[a][r][32 + lane]); }
            u0 = t[0][0]; u1 = t[1][0];
#pragma unroll
            for (int r = 1; r < ORE; r++) {
              u0.x += t[0][r].x; u0.y += t[0][r].y; u0.z += t[0][r].z; u0.w += t[0][r].w;
              u1.x += t[1][r].x; u1.y += t[1][r].y; u1.z += t[1][r].z; u1.w += t[1][r].w;
            }
            if (__all_sync(0xffffffffu, u0.w == (float)TPH && u1.w == (float)TPH)) break;
            if (++it > (1u << 22)) __trap();
          }
          __nv_bfloat16* s16 = reinterpret_cast<__nv_bfloat16*>(stage);
          s16[3 * lane] = __float2bfloat16_rn(u0.x); s16[3 * lane + 1] = __float2bfloat16_rn(u0.y); s16[3 * lane + 2] = __float2bfloat16_rn(u0.z);
          s16[96 + 3 * lane] = __float2bfloat16_rn(u1.x); s16[96 + 3 * lane + 1] = __float2bfloat16_rn(u1.y); s16[96 + 3 * lane + 2] = __float2bfloat16_rn(u1.z);
        }
        __syncwarp();
        mbar_wait(my_full, use & 1);
        mbar_wait(my_full + 8, use & 1);
        float v0, v1;
        gemv_tile<12>(slot, stage, lane, v0, v1);
        __syncwarp();
        if (lane == 0) mbar_arrive(my_empty);
        if (type == T_WO) {
          red_add_v2(acc->attn + c0, v0, 1.0f);
          red_add_v2(acc->attn + c0 + 8, v1, 1.0f);
          if (lane == 0) PROF_STAMP(14);
        } else if (!last) {
          red[(NH - 1 - a) * 64 + 16 * j + g] = v0; red[(NH - 1 - a) * 64 + 16 * j + 8 + g] = v1;
          __syncwarp();
          if (lane == 0) mbar_arrive(bar_wf);
        } else {
          if (lane == 0) PROF_STAMP(32);
          const float ga0 = (g & 1) ? bf_hi(gw0.x) : bf_lo(gw0.x), ga1 = (g & 1) ? bf_hi(gw1.x) : bf_lo(gw1.x);
          mbar_wait(bar_wf, 0);
          if (lane == 0) PROF_STAMP(33);
#pragma unroll
          for (int w = 1; w < NWF; w++) { pre0 += red[w * 64 + 16 * j + g]; pre1 += red[w * 64 + 16 * j + 8 + g]; }
          const float x0 = bf16r(xs[c0] + bf16r(ga0 * bf16r(pre0 + v0)));
          const float x1 = bf16r(xs[c0 + 8] + bf16r(ga1 * bf16r(pre1 + v1)));
          const float n0 = __shfl_down_sync(0xffffffffu, x0, 4), n1 = __shfl_down_sync(0xffffffffu, x1, 4);
          if (!(g & 1)) {
            const uint32_t w0 = ~pack_bf16(x0, n0), w1 = ~pack_bf16(x1, n1);
#pragma unroll
            for (int r = 0; r < XRE; r++) {
              st_relaxed(&acc->llx1[r][c0 >> 1], w0);
              st_relaxed(&acc->llx1[r][(c0 + 8) >> 1], w1);
            }
          }
        }
      } else if (type == T_MS) {
        const uint32_t* va32 = reinterpret_cast<const uint32_t*>(smem + SM_VA);
        const int r0 = (lane & 7) + ((lane >> 4) << 3), lo = (lane >> 3) & 1;
        const uint32_t w = slot + r0 * 32 + ((lo ^ ((r0 >> 2) & 1)) << 4);
        float ma[4][4];
#pragma unroll
        for (int i = 0; i < 4; i++) { ma[i][0] = ma[i][1] = ma[i][2] = ma[i][3] = 0.f; }
        mbar_wait(my_full, use & 1);
        mbar_wait(my_full + 8, use & 1);
#pragma unroll 2
        for (int k4 = 0; k4 < 10; k4++) {
#pragma unroll
          for (int i = 0; i < 4; i++) {
            uint32_t af[4];
            ldsm4t(af, w + (4 * k4 + i) * 512);
            mma16816(ma[i], af, va32[8 * (4 * k4 + i) + j], va32[8 * (4 * k4 + i) + 4 + j]);
          }
        }
        __syncwarp();
        if (lane == 0) mbar_arrive(my_empty);
        const float v0 = (ma[0][0] + ma[1][0]) + (ma[2][0] + ma[3][0]), v1 = (ma[0][2] + ma[1][2]) + (ma[2][2] + ma[3][2]);
        const float n0 = __shfl_down_sync(0xffffffffu, v0, 4), n1 = __shfl_down_sync(0xffffffffu, v1, 4);
        if (!(g & 1)) {
          st_relaxed_v2(&g_llmod[j][b * 8 + (g >> 1)], pack_bf16(v0, n0), ep + 1);
          st_relaxed_v2(&g_llmod[j][b * 8 + 4 + (g >> 1)], pack_bf16(v1, n1), ep + 1);
        }
        if (lane == 0) PROF_STAMP(b < 120 ? 35 : 39);
      } else {
        break;
      }
    }
  }

  if (tid == 0) PROF_STAMP(9);
  uint32_t f1a[5][4], f1b[5][4], f2a[12][4];
  uint32_t sbp[4] = {0u, 0u, 0u, 0u}, cbp[4] = {0u, 0u, 0u, 0u};
  float gb = 0.f;
  const int gt = tid < 80 ? tid : tid - 16;
  const uint2* modp = g_llmod[cta & (QRE - 1)];
  auto mod_word = [&](int w) {
    uint2 v;
    uint32_t it = 0;
    do {
      v = ld_relaxed_v2(modp + w);
      if (++it > (1u << 22)) __trap();
    } while (v.y != ep + 1);
    return v.x;
  };
  if (has_f1) {
    if (tid < 96) {
      uint32_t it = 0;
      uint4 s0, s1, c0, c1;
      const unsigned tg = ep + 1;
      do {
        s0 = ld_relaxed_v4(modp + 3 * 320 + 4 * gt); s1 = ld_relaxed_v4(modp + 3 * 320 + 4 * gt + 2);
        c0 = ld_relaxed_v4(modp + 4 * 320 + 4 * gt); c1 = ld_relaxed_v4(modp + 4 * 320 + 4 * gt + 2);
        if (++it > (1u << 22)) __trap();
      } while (s0.y != tg || s0.w != tg || s1.y != tg || s1.w != tg || c0.y != tg || c0.w != tg || c1.y != tg || c1.w != tg);
      sbp[0] = s0.x; sbp[1] = s0.z; sbp[2] = s1.x; sbp[3] = s1.z;
      cbp[0] = pack_bf16(1.0f + bf_lo(c0.x), 1.0f + bf_hi(c0.x)); cbp[1] = pack_bf16(1.0f + bf_lo(c0.z), 1.0f + bf_hi(c0.z));
      cbp[2] = pack_bf16(1.0f + bf_lo(c1.x), 1.0f + bf_hi(c1.x)); cbp[3] = pack_bf16(1.0f + bf_lo(c1.z), 1.0f + bf_hi(c1.z));
    }
    __syncwarp();
    if (tid == 0) PROF_STAMP(34);
    mbar_wait(bar_tail + 0, 0);
    slice_frags(sb + tailslot[0] * SLOT_BYTES, warp, lane, f1a);
    mbar_wait(bar_tail + 8, 0);
    slice_frags(sb + tailslot[1] * SLOT_BYTES, warp, lane, f1b);
  }
  auto f2_preload = [&]() {
    if (tid < (has_f2b ? 32 : 16)) {
      const uint32_t w = mod_word(5 * 320 + (tid < 16 ? f2 : f2b) * 8 + ((tid & 15) >> 1));
      gb = (tid & 1) ? bf_hi(w) : bf_lo(w);
    }
    __syncwarp();
    mbar_wait(bar_tail + 16 + 8 * (warp >> 2), 0);
    const int r0 = (lane & 7) + ((lane >> 4) << 3), lo = (lane >> 3) & 1;
    const uint32_t base = sb + tailslot[2 + (warp >> 2)] * SLOT_BYTES + ((warp & 3) * 192 + r0) * 32 + ((lo ^ ((r0 >> 2) & 1)) << 4);
#pragma unroll
    for (int ks = 0; ks < 12; ks++) ldsm4t(f2a[ks], base + ks * 512);
  };
  if (has_f2) f2_preload();
  if (tid == 0) PROF_STAMP(20);
  constexpr bool live = true;
  if (tid < 96) {
    uint4 v;
    uint32_t it = 0;
    do {
      v = ld_relaxed_v4(reinterpret_cast<const uint4*>(acc->llx1[cta & (XRE - 1)]) + gt);
      if (++it > (1u << 22)) __trap();
    } while (v.x == 0u || v.y == 0u || v.z == 0u || v.w == 0u);
    __syncwarp();
    if (tid == 0) PROF_STAMP(10);
    float x[8] = {bf_lo(~v.x), bf_hi(~v.x), bf_lo(~v.y), bf_hi(~v.y), bf_lo(~v.z), bf_hi(~v.z), bf_lo(~v.w), bf_hi(~v.w)};
    if (has_f2) {
      float4* xd = reinterpret_cast<float4*>(xs) + 2 * gt;
      xd[0] = make_float4(x[0], x[1], x[2], x[3]);
      xd[1] = make_float4(x[4], x[5], x[6], x[7]);
    }
    if (has_f1) {
      float m = (((x[0] + x[1]) + (x[2] + x[3])) + ((x[4] + x[5]) + (x[6] + x[7]))) * 0.125f;
      float q = 0.f, q2 = 0.f;
#pragma unroll
      for (int e = 0; e < 4; e++) {
        const float d0 = x[e] - m, d1 = x[4 + e] - m;
        q = fmaf(d0, d0, q); q2 = fmaf(d1, d1, q2);
      }
      q += q2;
#pragma unroll
      for (int o = 0; o < 5; o++) {
        const float mo = __shfl_xor_sync(0xffffffffu, m, 1 << o), qo = __shfl_xor_sync(0xffffffffu, q, 1 << o);
        const float d = mo - m;
        m = 0.5f * (m + mo);
        q = fmaf(d * d, (float)(4 << o), q + qo);
      }
      float* stat = red + 384;
      if (lane == 0) { stat[2 * warp] = m; stat[2 * warp + 1] = q; }
      asm volatile("bar.sync 4, 96;" ::: "memory");
      const float m0 = stat[0], q0 = stat[1], m1 = stat[2], q1 = stat[3], m2 = stat[4], qd = stat[5];
      const float mean = (0.4f * (m0 + m1)) + 0.2f * m2;
      const float e0 = m0 - mean, e1 = m1 - mean, e2 = m2 - mean;
      const float var = (q0 + q1 + 0.5f * qd + 256.f * (e0 * e0 + e1 * e1) + 128.f * e2 * e2) * (1.0f / D_MODEL);
      const float mean_b = bf16r(mean);
      float sd, rstd;
      asm("sqrt.approx.ftz.f32 %0, %1;" : "=f"(sd) : "f"(bf16r(bf16r(var) + 1e-5f)));
      asm("rcp.approx.ftz.f32 %0, %1;" : "=f"(rstd) : "f"(bf16r(sd)));
      uint32_t h[4];
#pragma unroll
      for (int e = 0; e < 4; e++) {
        const uint32_t a = pack_bf16(x[2 * e] - mean_b, x[2 * e + 1] - mean_b);
        const uint32_t nn = pack_bf16(bf_lo(a) * rstd, bf_hi(a) * rstd);
        const uint32_t t = pack_bf16(bf_lo(nn) * bf_lo(cbp[e]), bf_hi(nn) * bf_hi(cbp[e]));
        h[e] = pack_bf16(bf_lo(t) + bf_lo(sbp[e]), bf_hi(t) + bf_hi(sbp[e]));
      }
      reinterpret_cast<uint4*>(vh)[gt] = make_uint4(h[0], h[1], h[2], h[3]);
    }
    __syncwarp();
  }
  cons_bar();
  if (live && tid == 0) PROF_STAMP(21);
  if (has_f1) {
    uint32_t bf[10];
    vec_frags(vh, warp, lane, bf);
    slice_mma(f1a, bf, red, warp, lane);
    slice_mma(f1b, bf, red + 128, warp, lane);
    if (live && tid == 0) PROF_STAMP(61);
    cons_bar();
    if (live && tid == 0) PROF_STAMP(62);
    if (warp == 0) {
      const float v = bf16r(red8(red, lane));
      const float up = __shfl_down_sync(0xffffffffu, v, 16);
      const float hh = bf16r(bf16r(silu_f(v)) * up);
      const float hn = __shfl_down_sync(0xffffffffu, hh, 1);
      const uint32_t hw = ~pack_bf16(hh, hn);
      const int wi = lane >> 1;
      if (live && lane < 16 && !(lane & 1)) st_relaxed(&acc->llhh[16 * (cta >> 1) + 4 * (wi & 3) + 2 * (cta & 1) + (wi >> 2)], hw);
      if (live && lane == 0) PROF_STAMP(11);
      __syncwarp();
    }
  }
  if (has_f2) {
    uint4 hv[6];
    {
      uint32_t pend = live ? 0x3f : 0, it = 0;
#pragma unroll
      for (int t = 0; t < 6; t++) hv[t] = make_uint4(0u, 0u, 0u, 0u);
      const uint4* src = reinterpret_cast<const uint4*>(acc->llhh) + 24 * warp + j;
      while (pend) {
#pragma unroll
        for (int t = 0; t < 6; t++)
          if ((pend >> t) & 1u) hv[t] = ld_relaxed_v4(src + 4 * t);
#pragma unroll
        for (int t = 0; t < 6; t++)
          if (hv[t].x != 0u && hv[t].y != 0u && hv[t].z != 0u && hv[t].w != 0u) pend &= ~(1u << t);
        if (++it > (1u << 22)) __trap();
      }
      __syncwarp();
    }
    if (live && tid == 0) PROF_STAMP(12);
    float oa[4][4];
#pragma unroll
    for (int i = 0; i < 4; i++) { oa[i][0] = oa[i][1] = oa[i][2] = oa[i][3] = 0.f; }
#pragma unroll
    for (int t = 0; t < 6; t++) {
      mma16816(oa[(2 * t) & 3], f2a[2 * t], ~hv[t].x, ~hv[t].y);
      mma16816(oa[(2 * t + 1) & 3], f2a[2 * t + 1], ~hv[t].z, ~hv[t].w);
    }
    float* red2 = red + 256;
    if (j == 0) {
      red2[g * 8 + warp] = (oa[0][0] + oa[1][0]) + (oa[2][0] + oa[3][0]);
      red2[(8 + g) * 8 + warp] = (oa[0][2] + oa[1][2]) + (oa[2][2] + oa[3][2]);
    }
    if (has_f2b) {
      mbar_wait(bar_tail + 8 * (warp >> 2), 0);
      const int r0 = (lane & 7) + ((lane >> 4) << 3), lo = (lane >> 3) & 1;
      const uint32_t base = sb + tailslot[warp >> 2] * SLOT_BYTES + ((warp & 3) * 192 + r0) * 32 + ((lo ^ ((r0 >> 2) & 1)) << 4);
#pragma unroll
      for (int i = 0; i < 4; i++) { oa[i][0] = oa[i][1] = oa[i][2] = oa[i][3] = 0.f; }
#pragma unroll
      for (int t = 0; t < 6; t++) {
        uint32_t a0[4], a1[4];
        ldsm4t(a0, base + (2 * t) * 512);
        ldsm4t(a1, base + (2 * t + 1) * 512);
        mma16816(oa[(2 * t) & 3], a0, ~hv[t].x, ~hv[t].y);
        mma16816(oa[(2 * t + 1) & 3], a1, ~hv[t].z, ~hv[t].w);
      }
      if (j == 0) {
        red2[(16 + g) * 8 + warp] = (oa[0][0] + oa[1][0]) + (oa[2][0] + oa[3][0]);
        red2[(24 + g) * 8 + warp] = (oa[0][2] + oa[1][2]) + (oa[2][2] + oa[3][2]);
      }
    }
    cons_bar();
    if (tid < (has_f2b ? 32 : 16)) {
      const int col = (tid < 16 ? f2 : f2b) * 16 + (tid & 15);
      prm.out[col] = __float2bfloat16_rn(xs[col] + bf16r(gb * bf16r(red8(red2, tid))));
    }
    if (live && tid == 0) PROF_STAMP(13);
  }
  if (tid == 0) PROF_SYNC(30);
}

typedef CUresult (*EncodeFn)(CUtensorMap*, CUtensorMapDataType, cuuint32_t, void*, const cuuint64_t*,
                             const cuuint64_t*, const cuuint32_t*, const cuuint32_t*, CUtensorMapInterleave,
                             CUtensorMapSwizzle, CUtensorMapL2promotion, CUtensorMapFloatOOBfill);

void make_map(EncodeFn fn, CUtensorMap* tm, const void* base, int rank, const cuuint64_t* dims,
              const cuuint64_t* strides, const cuuint32_t* box, CUtensorMapSwizzle sw, CUtensorMapL2promotion pr) {
  cuuint32_t es[3] = {1, 1, 1};
  fn(tm, CU_TENSOR_MAP_DATA_TYPE_BFLOAT16, rank, const_cast<void*>(base), dims, strides, box, es,
     CU_TENSOR_MAP_INTERLEAVE_NONE, sw, pr, CU_TENSOR_MAP_FLOAT_OOB_FILL_NONE);
}

}

extern "C" void kernel_launch(void* const* d_in, const int* in_sizes, int n_in, void* d_out, int out_size) {
  (void)in_sizes; (void)n_in; (void)out_size;
  static EncodeFn encode = nullptr;
  static int num_sms = 0;
  if (!encode) {
    void* fn = nullptr;
    cudaDriverEntryPointQueryResult qr;
    cudaGetDriverEntryPoint("cuTensorMapEncodeTiled", &fn, cudaEnableDefault, &qr);
    encode = reinterpret_cast<EncodeFn>(fn);
    cudaDeviceGetAttribute(&num_sms, cudaDevAttrMultiProcessorCount, 0);
    cudaFuncSetAttribute(fused_kernel, cudaFuncAttributeMaxDynamicSharedMemorySize, SM_TOTAL);
  }
  CUtensorMap tmK, tmV, tmWq, tmWmodS, tmWo, tmW1, tmW3, tmW2;
  const CUtensorMapL2promotion P128 = CU_TENSOR_MAP_L2_PROMOTION_L2_128B, P256 = CU_TENSOR_MAP_L2_PROMOTION_L2_256B;
  {
    cuuint64_t dims[2] = {64, (cuuint64_t)NH * SK * 3}, str[1] = {128};
    cuuint32_t box[2] = {64, 96};
    make_map(encode, &tmK, d_in[1], 2, dims, str, box, CU_TENSOR_MAP_SWIZZLE_128B, P256);
    make_map(encode, &tmV, d_in[2], 2, dims, str, box, CU_TENSOR_MAP_SWIZZLE_128B, P256);
  }
  {
    cuuint64_t dims[2] = {NH * DH, D_MODEL}, str[1] = {NH * DH * 2};
    cuuint32_t box[2] = {64, 80};
    make_map(encode, &tmWq, d_in[3], 2, dims, str, box, CU_TENSOR_MAP_SWIZZLE_128B, P128);
  }
  {
    cuuint64_t dims3[3] = {6 * D_MODEL, 128, 5}, str3[2] = {6 * D_MODEL * 2, 128 * 6 * D_MODEL * 2};
    cuuint32_t box3[3] = {16, 128, 5};
    make_map(encode, &tmWmodS, d_in[10], 3, dims3, str3, box3, CU_TENSOR_MAP_SWIZZLE_32B, P128);
  }
  {
    cuuint64_t dims[2] = {D_MODEL, NH * DH}, str[1] = {D_MODEL * 2};
    cuuint32_t box[2] = {64, 96};
    make_map(encode, &tmWo, d_in[4], 2, dims, str, box, CU_TENSOR_MAP_SWIZZLE_128B, P128);
  }
  {
    cuuint64_t dims[3] = {FF, 128, 5}, str[2] = {FF * 2, 128 * FF * 2};
    cuuint32_t box[3] = {16, 128, 5};
    make_map(encode, &tmW1, d_in[6], 3, dims, str, box, CU_TENSOR_MAP_SWIZZLE_32B, P128);
    make_map(encode, &tmW3, d_in[7], 3, dims, str, box, CU_TENSOR_MAP_SWIZZLE_32B, P128);
  }
  {
    cuuint64_t dims[3] = {D_MODEL, 256, 6}, str[2] = {D_MODEL * 2, 256 * D_MODEL * 2};
    cuuint32_t box[3] = {16, 256, 3};
    make_map(encode, &tmW2, d_in[8], 3, dims, str, box, CU_TENSOR_MAP_SWIZZLE_32B, P128);
  }
  Params prm;
  prm.x = (const __nv_bfloat16*)d_in[0];
  prm.c = (const __nv_bfloat16*)d_in[9];
  prm.wmod = (const char*)d_in[10];
  prm.wq = (const char*)d_in[3];
  prm.kc = (const char*)d_in[1];
  prm.out = (__nv_bfloat16*)d_out;
  fused_kernel<<<num_sms, NTHREADS, SM_TOTAL, cudaStreamPerThread>>>(tmK, tmV, tmWq, tmWmodS, tmWo, tmW1, tmW3, tmW2, prm);
}
```

```cpp
#include <cuda_runtime.h>
#include <cuda_bf16.h>
#include <cuda.h>
#include <stdint.h>

namespace {

constexpr int D_MODEL = 640;
constexpr int NH = 32;
constexpr int SK = 8192;
constexpr int DH = 192;
constexpr int FF = 1536;
constexpr int TPH = 128;
constexpr int NS = 8;
constexpr int SLOT_BYTES = 24576;
constexpr int NCW = 8;
constexpr int W_PROD = NCW, W_JAN = NCW + 1, W_GATH = NCW + 2;
constexpr int NTHREADS = (NCW + 3) * 32;
#define WINDOW 5
#define WIN_HEAD 5
#define WIN_WQ 5
#define KDELAY 0
#define WIN_CATCH 8
#define CATCH_ITEMS 5
#define WIN_TAIL 2
#define WF_LEAD (NWF * 128 + 128 + N_MS)
#define WIN_FFN 3
#define SHALLOW_LEAD 720
#define SMALLW 1
#define WOPF_AHEAD 2
#define TAIL_LEAD 0
#define SLOW_LEAD 0
#define NSTAT 10
constexpr int NSTATIC = NSTAT;
#define PF_CYCLES 1800
#define ORE 4
#define LAG 1
constexpr int QRE = 4;
constexpr int XRE = 4;

constexpr int N_H1 = 80;
constexpr int N_H3 = 96;
constexpr int N_MS = 160;
#define NWF 3
constexpr int N_WO = (NH - NWF) * 10;
constexpr int NK = NH * TPH;
constexpr int NSEQ = NK + NK + N_WO + N_MS;
#define MS_BACK 256
#define N_MSA 40
#define MS_AT (NSEQ - N_MS - MS_BACK)
constexpr int WF_CTA0 = 96;

constexpr int N_F1 = 96;
constexpr int N_F2 = 40;

enum { T_K = 1, T_V = 2, T_WO = 3, T_MS = 4, T_WF = 5, T_END = 15 };

struct __align__(128) Ctr { unsigned v; unsigned pad[31]; };
struct __align__(128) Acc {
  Ctr cntK[NH], hintV[NH];
  float2 tstat[NH * TPH];
  float2 hstat[NH];
  float4 o[NH][ORE][DH / 3];
  float2 attn[D_MODEL];
  uint32_t llx1[XRE][D_MODEL / 2];
  uint32_t llhh[FF / 2];
};
struct __align__(128) Par {
  Ctr ticket, hintH3;
  uint32_t llq[QRE][NH * DH / 2];
};
static_assert(sizeof(Acc) % 16 == 0 && sizeof(Par) % 16 == 0, "");

__device__ Acc g_acc;
__device__ Par g_par[2];
__device__ __align__(128) uint2 g_llmod[QRE][3 * D_MODEL];
__device__ unsigned g_epoch;
__device__ volatile unsigned g_sink;
__device__ __align__(128) uint2 g_sc[NH * SK / 2];

#define PROF_STAMP(i) do {} while (0)
#define PROF_SYNC(i) do {} while (0)

constexpr int SM_SLOTS = 0;
constexpr int SM_STAGE = SM_SLOTS + NS * SLOT_BYTES;
constexpr int SM_Q = SM_STAGE + NCW * 768;
constexpr int SM_VA = SM_Q + NH * DH * 2;
constexpr int SM_VH = SM_VA + D_MODEL * 2;
constexpr int SM_X = SM_VH + D_MODEL * 2;
constexpr int SM_RED = SM_X + D_MODEL * 4;
constexpr int SM_BAR = SM_RED + 64 * 8 * 4;
constexpr int SM_DESC = SM_BAR + 40 * 8;
constexpr int SM_TOTAL = SM_DESC + 64;
static_assert(SM_TOTAL <= 232448, "");

struct Params {
  const __nv_bfloat16* x;
  const __nv_bfloat16* c;
  const char* wmod;
  const char* wq;
  const char* kc;
  const char* wo;
  __nv_bfloat16* out;
};

#define NSLEEP do {} while (0)
__device__ __forceinline__ uint32_t smem_u32(const void* p) { return (uint32_t)__cvta_generic_to_shared(p); }
__device__ __forceinline__ void mbar_init(uint32_t bar, uint32_t cnt) {
  asm volatile("mbarrier.init.shared::cta.b64 [%0], %1;" ::"r"(bar), "r"(cnt) : "memory");
}
__device__ __forceinline__ void mbar_expect_tx(uint32_t bar, uint32_t bytes) {
  asm volatile("mbarrier.arrive.expect_tx.shared::cta.b64 _, [%0], %1;" ::"r"(bar), "r"(bytes) : "memory");
}
__device__ __forceinline__ void mbar_arrive(uint32_t bar) {
  asm volatile("mbarrier.arrive.shared::cta.b64 _, [%0];" ::"r"(bar) : "memory");
}
__device__ __forceinline__ bool mbar_try(uint32_t bar, uint32_t parity) {
  uint32_t ok;
  asm volatile(
      "{\n.reg .pred p;\nmbarrier.try_wait.parity.shared::cta.b64 p, [%1], %2;\nselp.u32 %0, 1, 0, p;\n}"
      : "=r"(ok) : "r"(bar), "r"(parity) : "memory");
  return ok != 0;
}
__device__ __forceinline__ bool mbar_test(uint32_t bar, uint32_t parity) {
  uint32_t ok;
  asm volatile(
      "{\n.reg .pred p;\nmbarrier.test_wait.parity.shared::cta.b64 p, [%1], %2;\nselp.u32 %0, 1, 0, p;\n}"
      : "=r"(ok) : "r"(bar), "r"(parity) : "memory");
  return ok != 0;
}
__device__ __forceinline__ void mbar_wait(uint32_t bar, uint32_t parity) {
  uint32_t it = 0;
  while (!mbar_try(bar, parity)) {
    if (++it > (1u << 24)) __trap();
  }
}
__device__ __forceinline__ void tma_2d(uint32_t dst, const CUtensorMap* tm, int c0, int c1, uint32_t bar, uint64_t pol) {
  asm volatile(
      "cp.async.bulk.tensor.2d.shared::cluster.global.mbarrier::complete_tx::bytes.L2::cache_hint [%0], [%1, {%3, %4}], [%2], %5;"
      ::"r"(dst), "l"(tm), "r"(bar), "r"(c0), "r"(c1), "l"(pol) : "memory");
}
__device__ __forceinline__ void tma_3d(uint32_t dst, const CUtensorMap* tm, int c0, int c1, int c2, uint32_t bar) {
  asm volatile(
      "cp.async.bulk.tensor.3d.shared::cluster.global.mbarrier::complete_tx::bytes [%0], [%1, {%3, %4, %5}], [%2];"
      ::"r"(dst), "l"(tm), "r"(bar), "r"(c0), "r"(c1), "r"(c2) : "memory");
}
__device__ __forceinline__ void prefetch_tm(const CUtensorMap* tm) {
  asm volatile("prefetch.tensormap [%0];" ::"l"(tm) : "memory");
}
__device__ __forceinline__ void ldsm4(uint32_t (&a)[4], uint32_t addr) {
  asm volatile("ldmatrix.sync.aligned.m8n8.x4.shared.b16 {%0,%1,%2,%3}, [%4];"
               : "=r"(a[0]), "=r"(a[1]), "=r"(a[2]), "=r"(a[3]) : "r"(addr) : "memory");
}
__device__ __forceinline__ void ldsm4t(uint32_t (&a)[4], uint32_t addr) {
  asm volatile("ldmatrix.sync.aligned.m8n8.x4.trans.shared.b16 {%0,%1,%2,%3}, [%4];"
               : "=r"(a[0]), "=r"(a[1]), "=r"(a[2]), "=r"(a[3]) : "r"(addr) : "memory");
}
__device__ __forceinline__ void mma16816(float (&d)[4], const uint32_t (&a)[4], uint32_t b0, uint32_t b1) {
  asm volatile(
      "mma.sync.aligned.m16n8k16.row.col.f32.bf16.bf16.f32 {%0,%1,%2,%3}, {%4,%5,%6,%7}, {%8,%9}, {%0,%1,%2,%3};"
      : "+f"(d[0]), "+f"(d[1]), "+f"(d[2]), "+f"(d[3])
      : "r"(a[0]), "r"(a[1]), "r"(a[2]), "r"(a[3]), "r"(b0), "r"(b1));
}
__device__ __forceinline__ unsigned ld_acquire(const unsigned* p) {
  unsigned v;
  asm volatile("ld.acquire.gpu.global.u32 %0, [%1];" : "=r"(v) : "l"(p) : "memory");
  return v;
}
__device__ __forceinline__ unsigned ld_relaxed(const unsigned* p) {
  unsigned v;
  asm volatile("ld.relaxed.gpu.global.u32 %0, [%1];" : "=r"(v) : "l"(p) : "memory");
  return v;
}
__device__ __forceinline__ float2 ld_relaxed_f2(const float* p) {
  float2 v;
  asm volatile("ld.relaxed.gpu.global.v2.f32 {%0,%1}, [%2];" : "=f"(v.x), "=f"(v.y) : "l"(p) : "memory");
  return v;
}
__device__ __forceinline__ float ld_relaxed_f(const float* p) {
  float v;
  asm volatile("ld.relaxed.gpu.global.f32 %0, [%1];" : "=f"(v) : "l"(p) : "memory");
  return v;
}
__device__ __forceinline__ uint2 ld_relaxed_v2(const uint2* p) {
  uint2 v;
  asm volatile("ld.relaxed.gpu.global.v2.u32 {%0,%1}, [%2];" : "=r"(v.x), "=r"(v.y) : "l"(p) : "memory");
  return v;
}
__device__ __forceinline__ uint4 ld_relaxed_v4(const void* p) {
  uint4 v;
  asm volatile("ld.relaxed.gpu.global.v4.u32 {%0,%1,%2,%3}, [%4];" : "=r"(v.x), "=r"(v.y), "=r"(v.z), "=r"(v.w) : "l"(p) : "memory");
  return v;
}
__device__ __forceinline__ void st_relaxed_v2(uint2* p, uint32_t a, uint32_t b) {
  asm volatile("st.relaxed.gpu.global.v2.u32 [%0], {%1, %2};" ::"l"(p), "r"(a), "r"(b) : "memory");
}
__device__ __forceinline__ void st_relaxed(unsigned* p, unsigned v) {
  asm volatile("st.relaxed.gpu.global.u32 [%0], %1;" ::"l"(p), "r"(v) : "memory");
}
__device__ __forceinline__ void fence_gpu() { asm volatile("fence.acq_rel.gpu;" ::: "memory"); }
__device__ __forceinline__ float atom_add_f32(float* p, float v) {
  float r;
  asm volatile("atom.relaxed.gpu.global.add.f32 %0, [%1], %2;" : "=f"(r) : "l"(p), "f"(v) : "memory");
  return r;
}
__device__ __forceinline__ void red_add_v4(float4* p, float a, float b, float c, float d) {
  asm volatile("red.relaxed.gpu.global.add.v4.f32 [%0], {%1, %2, %3, %4};" ::"l"(p), "f"(a), "f"(b), "f"(c), "f"(d) : "memory");
}
__device__ __forceinline__ void red_add_v2(float2* p, float a, float b) {
  asm volatile("red.relaxed.gpu.global.add.v2.f32 [%0], {%1, %2};" ::"l"(p), "f"(a), "f"(b) : "memory");
}
__device__ __forceinline__ float4 ld_relaxed_f4(const float4* p) {
  float4 v;
  asm volatile("ld.relaxed.gpu.global.v4.f32 {%0,%1,%2,%3}, [%4];" : "=f"(v.x), "=f"(v.y), "=f"(v.z), "=f"(v.w) : "l"(p) : "memory");
  return v;
}
__device__ __forceinline__ void red_add_u32(unsigned* p, unsigned v) {
  asm volatile("red.relaxed.gpu.global.add.u32 [%0], %1;" ::"l"(p), "r"(v) : "memory");
}
__device__ __forceinline__ void spin_ge(const unsigned* p, unsigned target) {
  uint32_t it = 0;
  while (ld_relaxed(p) < target) {
    if (++it > (1u << 22)) __trap();
  }
}
__device__ __forceinline__ void spin_ge_sleep(const unsigned* p, unsigned target) {
  uint32_t it = 0;
  while (ld_relaxed(p) < target) {
    NSLEEP;
    if (++it > (1u << 22)) __trap();
  }
}
__device__ __forceinline__ void cons_bar() { asm volatile("bar.sync 1, 256;" ::: "memory"); }

__device__ __forceinline__ uint32_t pack_bf16(float lo, float hi) {
  uint32_t r;
  asm("cvt.rn.bf16x2.f32 %0, %1, %2;" : "=r"(r) : "f"(hi), "f"(lo));
  return r;
}
__device__ __forceinline__ float bf16r(float x) { return __uint_as_float(pack_bf16(0.f, x) & 0xffff0000u); }
__device__ __forceinline__ float bf_lo(uint32_t v) { return __uint_as_float(v << 16); }
__device__ __forceinline__ float bf_hi(uint32_t v) { return __uint_as_float(v & 0xffff0000u); }
__device__ __forceinline__ float warp_sum(float v) {
#pragma unroll
  for (int o = 16; o > 0; o >>= 1) v += __shfl_xor_sync(0xffffffffu, v, o);
  return v;
}
__device__ __forceinline__ float warp_max(float v) {
#pragma unroll
  for (int o = 16; o > 0; o >>= 1) v = fmaxf(v, __shfl_xor_sync(0xffffffffu, v, o));
  return v;
}
__device__ __forceinline__ float fast_exp(float x) {
  float r;
  asm("ex2.approx.ftz.f32 %0, %1;" : "=f"(r) : "f"(x * 1.4426950408889634f));
  return r;
}
__device__ __forceinline__ float silu_f(float x) {
  float r;
  asm("rcp.approx.f32 %0, %1;" : "=f"(r) : "f"(1.0f + fast_exp(-x)));
  return x * r;
}
__device__ __forceinline__ float sel4(int j, float a, float b, float c, float d) {
  float lo = (j & 1) ? b : a, hi = (j & 1) ? d : c;
  return (j & 2) ? hi : lo;
}

__device__ __forceinline__ void signal_after(unsigned* ctr, uint32_t dep, int lane) {
  const unsigned any = __ballot_sync(0xffffffffu, dep == 0x7fc5a5a5u);
  if (any) g_sink = any;
  if (lane == 0) red_add_u32(ctr, 1u);
}

template <int KS>
__device__ __forceinline__ void gemv_tile(uint32_t slot, const uint32_t* vec32, int lane, float& v0, float& v1) {
  const int j = lane & 3;
  const int r0 = (lane & 7) + ((lane >> 4) << 3), lo = (lane >> 3) & 1;
  const uint32_t vg = slot + r0 * 128 + ((lo ^ (r0 & 7)) << 4);
  float acc[3][4][4];
#pragma unroll
  for (int c = 0; c < 3; c++)
#pragma unroll
    for (int m = 0; m < 4; m++) { acc[c][m][0] = acc[c][m][1] = acc[c][m][2] = acc[c][m][3] = 0.f; }
#pragma unroll
  for (int ks = 0; ks < KS; ks++) {
    const uint32_t b0 = vec32[8 * ks + j], b1 = vec32[8 * ks + 4 + j];
#pragma unroll
    for (int m = 0; m < 4; m++) {
      uint32_t a[4];
      ldsm4t(a, (vg + ks * 2048) ^ (m << 5));
      mma16816(acc[ks % 3][m], a, b0, b1);
    }
  }
  float r0v[4], r2v[4];
#pragma unroll
  for (int m = 0; m < 4; m++) {
    r0v[m] = acc[0][m][0] + acc[1][m][0] + acc[2][m][0];
    r2v[m] = acc[0][m][2] + acc[1][m][2] + acc[2][m][2];
  }
  v0 = sel4(j, r0v[0], r0v[1], r0v[2], r0v[3]);
  v1 = sel4(j, r2v[0], r2v[1], r2v[2], r2v[3]);
}

__device__ __forceinline__ void slice_frags(uint32_t slot, int warp, int lane, uint32_t (&af)[5][4]) {
  const int r0 = (lane & 7) + ((lane >> 4) << 3), lo = (lane >> 3) & 1;
  const uint32_t w = slot + (warp * 80 + r0) * 32 + ((lo ^ ((r0 >> 2) & 1)) << 4);
#pragma unroll
  for (int ks = 0; ks < 5; ks++) ldsm4t(af[ks], w + ks * 512);
}
__device__ __forceinline__ void slice_mma(const uint32_t (&af)[5][4], const uint32_t (&b)[10], float* red, int warp, int lane) {
  float a[3][4];
#pragma unroll
  for (int i = 0; i < 3; i++) { a[i][0] = a[i][1] = a[i][2] = a[i][3] = 0.f; }
#pragma unroll
  for (int ks = 0; ks < 5; ks++) mma16816(a[ks % 3], af[ks], b[2 * ks], b[2 * ks + 1]);
  if ((lane & 3) == 0) {
    red[(lane >> 2) * 8 + warp] = a[0][0] + a[1][0] + a[2][0];
    red[(8 + (lane >> 2)) * 8 + warp] = a[0][2] + a[1][2] + a[2][2];
  }
}
__device__ __forceinline__ void vec_frags(const uint32_t* vec32, int warp, int lane, uint32_t (&b)[10]) {
#pragma unroll
  for (int ks = 0; ks < 5; ks++) {
    b[2 * ks] = vec32[40 * warp + 8 * ks + (lane & 3)];
    b[2 * ks + 1] = vec32[40 * warp + 8 * ks + 4 + (lane & 3)];
  }
}
__device__ __forceinline__ float red8(const float* red, int col) {
  const float4 a = *reinterpret_cast<const float4*>(red + col * 8), b = *reinterpret_cast<const float4*>(red + col * 8 + 4);
  return ((a.x + a.y) + (a.z + a.w)) + ((b.x + b.y) + (b.z + b.w));
}

__device__ __forceinline__ void ln_stats(const float* xs, int lane, float& mean_b, float& rstd) {
  const float k0 = xs[0];
  float s1[4] = {0.f, 0.f, 0.f, 0.f}, s2[4] = {0.f, 0.f, 0.f, 0.f};
#pragma unroll
  for (int i = 0; i < 5; i++) {
    const float4 v = reinterpret_cast<const float4*>(xs)[lane + 32 * i];
    const float d0 = v.x - k0, d1 = v.y - k0, d2 = v.z - k0, d3 = v.w - k0;
    s1[0] += d0; s1[1] += d1; s1[2] += d2; s1[3] += d3;
    s2[0] = fmaf(d0, d0, s2[0]); s2[1] = fmaf(d1, d1, s2[1]); s2[2] = fmaf(d2, d2, s2[2]); s2[3] = fmaf(d3, d3, s2[3]);
  }
  float a = (s1[0] + s1[1]) + (s1[2] + s1[3]), b = (s2[0] + s2[1]) + (s2[2] + s2[3]);
#pragma unroll
  for (int o = 16; o > 0; o >>= 1) {
    a += __shfl_xor_sync(0xffffffffu, a, o);
    b += __shfl_xor_sync(0xffffffffu, b, o);
  }
  const float md = a * (1.0f / D_MODEL);
  const float var = fmaxf(fmaf(-md, md, b * (1.0f / D_MODEL)), 0.f);
  mean_b = bf16r(k0 + md);
  float sd;
  asm("sqrt.approx.ftz.f32 %0, %1;" : "=f"(sd) : "f"(bf16r(bf16r(var) + 1e-5f)));
  asm("rcp.approx.ftz.f32 %0, %1;" : "=f"(rstd) : "f"(bf16r(sd)));
}
__device__ __forceinline__ uint32_t ln_mod2(float x0, float x1, float mean_b, float rstd, uint32_t cpair, uint32_t spair) {
  const uint32_t c1 = pack_bf16(1.0f + bf_lo(cpair), 1.0f + bf_hi(cpair));
  const uint32_t a = pack_bf16(x0 - mean_b, x1 - mean_b);
  const uint32_t n = pack_bf16(bf_lo(a) * rstd, bf_hi(a) * rstd);
  const uint32_t t = pack_bf16(bf_lo(n) * bf_lo(c1), bf_hi(n) * bf_hi(c1));
  return pack_bf16(bf_lo(t) + bf_lo(spair), bf_hi(t) + bf_hi(spair));
}

__global__ void __launch_bounds__(NTHREADS, 1)
fused_kernel(const __grid_constant__ CUtensorMap tmK, const __grid_constant__ CUtensorMap tmV,
             const __grid_constant__ CUtensorMap tmWq,
             const __grid_constant__ CUtensorMap tmWmodS,
             const __grid_constant__ CUtensorMap tmWo, const __grid_constant__ CUtensorMap tmW1,
             const __grid_constant__ CUtensorMap tmW3, const __grid_constant__ CUtensorMap tmW2,
             const Params prm) {
  extern __shared__ __align__(1024) unsigned char smem[];
  const uint32_t sb = smem_u32(smem);
  const int tid = threadIdx.x, warp = tid >> 5, lane = tid & 31;
  const int cta = blockIdx.x, G = gridDim.x;
  const uint32_t bar_full = sb + SM_BAR, bar_empty = bar_full + NS * 16, bar_post = bar_empty + NS * 8,
                 bar_tail = bar_post + NS * 8, bar_clear = bar_tail + 32, bar_mod = bar_clear + 8, bar_q = bar_mod + 8,
                 bar_wf = bar_q + 8;
  volatile uint32_t* desc = reinterpret_cast<volatile uint32_t*>(smem + SM_DESC);
  volatile uint32_t* tailslot = desc + 8;
  volatile uint32_t* s_epoch = desc + 12;
  Acc* const acc = &g_acc;
  const int h1 = cta - (G - N_H1);
  const int has_h1 = h1 >= 0 ? 1 : 0;
  const bool has_h3 = cta < N_H3;
  const int nh = has_h1 + (has_h3 ? 4 : 0);
  const bool has_f1 = cta < N_F1;
  const int f2 = G - 1 - cta;
  const bool has_f2 = cta >= N_F1 && f2 < N_F2;
  const int f2b = f2 + (G - N_F1);
  const bool has_f2b = has_f2 && f2b < N_F2;
  const int wf = cta - WF_CTA0;
  const bool has_wf = wf >= 0 && wf < 10;

  if (warp == W_PROD) {
    if (lane == 0) {
      PROF_SYNC(0);
      for (int i = 0; i < NS; i++) {
        mbar_init(bar_full + 16 * i, 1); mbar_init(bar_full + 16 * i + 8, 1);
        mbar_init(bar_empty + 8 * i, 1); mbar_init(bar_post + 8 * i, 1);
      }
      for (int i = 0; i < 7; i++) mbar_init(bar_tail + 8 * i, 1);
      mbar_init(bar_wf, NWF - 1);
      asm volatile("fence.mbarrier_init.release.cluster;" ::: "memory");
      asm volatile("fence.proxy.async.shared::cta;" ::: "memory");
      if (has_h1) {
        mbar_expect_tx(bar_full, 320 * 32);
        tma_3d(sb, &tmWmodS, h1 * 16, 0, 0, bar_full);
        mbar_expect_tx(bar_full + 8, 320 * 32);
        tma_3d(sb + 320 * 32, &tmWmodS, h1 * 16, 0, 5, bar_full + 8);
      }
      prefetch_tm(&tmWq);
      for (int i = 0; i < nh; i++) mbar_arrive(bar_post + 8 * i);
      prefetch_tm(&tmK);
      prefetch_tm(&tmV);
      prefetch_tm(&tmWo);
    }
    __syncwarp();
    asm volatile("bar.arrive 3, 64;" ::: "memory");
  } else if (warp == W_JAN) {
    uint4* z = reinterpret_cast<uint4*>(acc);
    constexpr int NZ = sizeof(Acc) / 16;
    const int per = (NZ + G - 1) / G;
    for (int i = cta * per + lane; i < min(NZ, (cta + 1) * per); i += 32) z[i] = make_uint4(0, 0, 0, 0);
    __syncwarp();
    if (lane == 0) fence_gpu();
    const unsigned e = *reinterpret_cast<volatile unsigned*>(&g_epoch);
    asm volatile("bar.sync 3, 64;" ::: "memory");
    if (lane == 0) { mbar_arrive(bar_clear); PROF_STAMP(4); }
    uint4* nx = reinterpret_cast<uint4*>(&g_par[(e & 1) ^ 1]);
    constexpr int NZP = sizeof(Par) / 16;
    for (int i = cta * 32 + lane; i < NZP; i += G * 32) nx[i] = make_uint4(0, 0, 0, 0);
    return;
  } else if (warp == W_GATH) {
    {
      const char* pa = lane < 3 ? prm.wmod + min(lane * (2 << 20) + h1 * 32 * (h1 >= 0), 6 * D_MODEL * D_MODEL * 2 - 128)
                     : lane < 7 ? prm.wq + min((lane - 3) * (2 << 20), NH * DH * D_MODEL * 2 - 128)
                                : prm.kc + (size_t)(lane - 7) * (2 << 20) + (size_t)(cta & 63) * SLOT_BYTES;
      if (lane < 16) asm volatile("prefetch.global.L2 [%0];" ::"l"(pa));
    }
    const uint4* src = reinterpret_cast<const uint4*>(g_llmod[cta & (QRE - 1)]) + lane;
    uint4 v[10];
#pragma unroll
    for (int i = 0; i < 10; i++) v[i] = ld_relaxed_v4(src + i * 32);
    const unsigned e = *reinterpret_cast<volatile unsigned*>(&g_epoch);
    if (lane == 0) *s_epoch = e;
    __syncwarp();
    asm volatile("bar.sync 0, %0;" ::"n"(NTHREADS - 32) : "memory");
    const unsigned tg = e + 1;
    uint32_t pend = 0x3ff, it = 0;
    for (;;) {
#pragma unroll
      for (int i = 0; i < 10; i++)
        if (((pend >> i) & 1u) && v[i].y == tg && v[i].w == tg) {
          reinterpret_cast<uint2*>(smem + SM_Q)[i * 32 + lane] = make_uint2(v[i].x, v[i].z);
          pend &= ~(1u << i);
        }
      if (!pend) break;
      NSLEEP;
#pragma unroll
      for (int i = 0; i < 10; i++)
        if ((pend >> i) & 1u) v[i] = ld_relaxed_v4(src + i * 32);
      if (++it > (1u << 22)) __trap();
    }
    __syncwarp();
    if (lane == 0) {
      PROF_STAMP(36);
      mbar_arrive(bar_mod);
      const unsigned* hint = &g_par[e & 1].hintH3.v;
      uint32_t it2 = 0;
      while (ld_acquire(hint) < (unsigned)G) {
        NSLEEP;
        if (++it2 > (1u << 22)) __trap();
      }
      PROF_STAMP(37);
      mbar_arrive(bar_q);
    }
    return;
  } else {
    uint32_t* va = reinterpret_cast<uint32_t*>(smem + SM_VA);
    float* xs = reinterpret_cast<float*>(smem + SM_X);
    const int p1 = tid + 256;
    const uint32_t cv0 = __ldg(reinterpret_cast<const uint32_t*>(prm.c) + tid);
    const uint32_t xv0 = __ldg(reinterpret_cast<const uint32_t*>(prm.x) + tid);
    uint32_t cv1 = 0, xv1 = 0;
    if (tid < 64) {
      cv1 = __ldg(reinterpret_cast<const uint32_t*>(prm.c) + p1);
      xv1 = __ldg(reinterpret_cast<const uint32_t*>(prm.x) + p1);
    }
    va[tid] = pack_bf16(silu_f(bf_lo(cv0)), silu_f(bf_hi(cv0)));
    xs[2 * tid] = bf_lo(xv0);
    xs[2 * tid + 1] = bf_hi(xv0);
    if (tid < 64) {
      va[p1] = pack_bf16(silu_f(bf_lo(cv1)), silu_f(bf_hi(cv1)));
      xs[2 * p1] = bf_lo(xv1);
      xs[2 * p1 + 1] = bf_hi(xv1);
    }
  }
  asm volatile("bar.sync 0, %0;" ::"n"(NTHREADS - 32) : "memory");
  const unsigned ep = *s_epoch;
  Par* const par = &g_par[ep & 1];

  if (warp == W_PROD) {
    if (lane != 0) return;
    uint64_t pol;
    asm volatile("createpolicy.fractional.L2::evict_first.b64 %0, 1.0;" : "=l"(pol));
    uint32_t tkA = atomicAdd(&par->ticket.v, 1u);
    uint32_t tkB = atomicAdd(&par->ticket.v, 1u);
    int win = WIN_WQ;
    bool head_phase = true;
    unsigned long long fifo = 0;
    int nfifo = 0;
    auto throttle = [&]() {
      if (nfifo >= win) {
        const uint32_t e = (uint32_t)(fifo >> (7 * (win - 1))) & 127u;
        mbar_wait(bar_full + 8 * (e >> 1), e & 1u);
      }
    };
    auto push = [&](uint32_t idx, uint32_t parity) { fifo = (fifo << 7) | (idx << 1) | parity; nfifo++; };
    uint32_t active = (1u << NS) - 1, used = 0, upar = 0;
    int cur = 0;
    auto acquire = [&]() {
      const int s = cur;
      do { cur = (cur + 1) & (NS - 1); } while (!((active >> cur) & 1u));
      if ((used >> s) & 1u) mbar_wait(bar_empty + 8 * s, ((upar >> s) & 1u) ^ 1u);
      return s;
    };
    auto post = [&](int s, uint32_t d) {
      desc[s] = d;
      mbar_arrive(bar_post + 8 * s);
    };
    auto issue_half = [&](int s, int h, const CUtensorMap* tm, int c0, int c1, uint32_t bytes, uint32_t dst) {
      throttle();
      const uint32_t bar = bar_full + 16 * s + 8 * h;
      mbar_expect_tx(bar, bytes);
      tma_2d(dst, tm, c0, c1, bar, pol);
      push(2 * s + h, (upar >> s) & 1u);
    };
    auto issue_small = [&](int s, int h, const CUtensorMap* tm, int c0, int z, uint32_t bytes) {
      throttle();
      const uint32_t bar = bar_full + 16 * s + 8 * h;
      mbar_expect_tx(bar, bytes);
      tma_3d(sb + s * SLOT_BYTES + h * bytes, tm, c0, 0, z, bar);
#pragma unroll
      for (int i = 0; i < SMALLW; i++) push(2 * s + h, (upar >> s) & 1u);
    };
    auto done_slot = [&](int s) { upar ^= 1u << s; used |= 1u << s; };
    if (has_h1) { acquire(); push(0, 0); push(1, 0); done_slot(0); }
    for (int i = has_h1; i < nh; i++) {
      const int s = acquire();
      issue_half(s, 0, &tmWq, cta * 64, (i - has_h1) * 160, 80 * 128, sb + s * SLOT_BYTES);
      issue_half(s, 1, &tmWq, cta * 64, (i - has_h1) * 160 + 80, 80 * 128, sb + s * SLOT_BYTES + 80 * 128);
      done_slot(s);
    }
    win = WIN_HEAD;
    int istat = 0;
    int wf_left = has_wf ? NWF : 0;
    bool tail_done = false, shallow = false;
    int pf_done = 0, catch_left = 0;
    for (;;) {
      uint32_t seq;
      if (istat < 0) {
        seq = NSEQ;
      } else if (istat < NSTATIC) {
        seq = cta + G * istat;
        istat++;
      } else {
        if (tkA == 0xfffffffeu) tkA = atomicAdd(&par->ticket.v, 1u);
        seq = tkA == 0xffffffffu ? NSEQ : NSTATIC * G + tkA;
        tkA = tkB;
        if (seq < NSEQ) {
          if (has_wf && seq >= NSEQ - WF_LEAD) {
            tkB = 0xffffffffu;
          } else if (!shallow && seq >= NSEQ - SHALLOW_LEAD) {
            shallow = true;
            tkB = 0xfffffffeu;
          } else if (shallow) {
            tkA = atomicAdd(&par->ticket.v, 1u);
          } else {
            tkB = atomicAdd(&par->ticket.v, 1u);
          }
        }
      }
      if (!tail_done && seq >= NSEQ - TAIL_LEAD && (seq < NSEQ || wf_left == 0)) {
        tail_done = true;
        win = WIN_FFN;
        const int nt = has_f1 ? 2 : has_f2b ? 4 : has_f2 ? 2 : 0;
        for (int k = 0; k < nt; k++) {
          const int ti = has_f1 ? k : (k + 2) & 3;
          const int s = acquire();
          active &= ~(1u << s);
          post(s, (uint32_t)T_END << 28);
          tailslot[ti] = s | (((upar >> s) & 1u) << 8);
          mbar_arrive(bar_tail + 8 * ti);
          if (has_f1) {
            issue_small(s, 0, ti == 0 ? &tmW1 : &tmW3, cta * 16, 0, 320 * 32);
            issue_small(s, 1, ti == 0 ? &tmW1 : &tmW3, cta * 16, 5, 320 * 32);
          } else {
            const int c0 = (ti >= 2 ? f2 : f2b) * 16, z = (ti & 1) * 6;
            issue_small(s, 0, &tmW2, c0, z, 384 * 32);
            issue_small(s, 1, &tmW2, c0, z + 3, 384 * 32);
          }
        }
      }
      int type, a, b;
      if (seq >= NSEQ) {
        if (wf_left == 0) break;
        type = T_WF; a = NH - wf_left; b = wf;
        wf_left--;
        istat = -1;
      } else if (seq >= MS_AT && seq < MS_AT + N_MSA) {
        type = T_MS; a = 0; b = N_H1 + (seq - MS_AT);
      } else if (seq >= NSEQ - (N_MS - N_MSA)) {
        type = T_MS; a = 0; b = N_H1 + N_MS - (NSEQ - seq);
      } else if (seq < NK + (MS_AT < NK ? N_MSA : 0)) {
        const uint32_t k = seq < MS_AT ? seq : seq - N_MSA;
        type = T_K; a = k >> 7; b = k & 127;
      } else {
        uint32_t r = seq - NK - (seq >= MS_AT ? N_MSA : 0);
        if (r < LAG * TPH) {
          type = T_V; a = r >> 7; b = r & 127;
        } else {
          r -= LAG * TPH;
          constexpr uint32_t NBLK = NH - NWF;
          const uint32_t blk = r / 138u, off = r - blk * 138u;
          if (blk < NBLK) {
            if (off < TPH) { type = T_V; a = LAG + blk; b = off; }
            else { type = T_WO; a = blk; b = off - TPH; }
          } else {
            r -= NBLK * 138u;
            type = T_V; a = LAG + NBLK + (r >> 7); b = r & 127;
          }
        }
      }
      if (head_phase && ((used >> cur) & 1u)) {
        int pf = istat;
        if (pf < pf_done) pf = pf_done;
        long long t_next = clock64();
        while (pf < NSTATIC && !mbar_test(bar_empty + 8 * cur, ((upar >> cur) & 1u) ^ 1u)) {
          if (clock64() >= t_next) {
            asm volatile("cp.async.bulk.prefetch.L2.global [%0], %1;" ::"l"(prm.kc + (size_t)(cta + G * pf) * SLOT_BYTES), "r"(SLOT_BYTES) : "memory");
            pf++;
            t_next += PF_CYCLES;
          }
        }
        pf_done = pf;
      }
      const int s = acquire();
      post(s, ((uint32_t)type << 28) | (a << 16) | b);
      if (head_phase && mbar_test(bar_q, 0)) { head_phase = false; win = WIN_CATCH; catch_left = CATCH_ITEMS; PROF_STAMP(43); }
      if (catch_left > 0 && --catch_left == 0) win = WINDOW;
      if (seq >= NSEQ - (N_MS - N_MSA) - SLOW_LEAD && type != T_WF && !tail_done) win = WIN_TAIL;
      const uint32_t dst = sb + s * SLOT_BYTES;
      if (type == T_MS) {
        issue_small(s, 0, &tmWmodS, b * 16, 0, 320 * 32);
        issue_small(s, 1, &tmWmodS, b * 16, 5, 320 * 32);
      } else {
        const CUtensorMap* tm = type == T_K ? &tmK : type == T_V ? &tmV : &tmWo;
        const int c0 = (type == T_K || type == T_V) ? 0 : b * 64;
        const int c1 = (type == T_K || type == T_V) ? (a * TPH + b) * 192 : a * DH;
        issue_half(s, 0, tm, c0, c1, 96 * 128, dst);
        issue_half(s, 1, tm, c0, c1 + 96, 96 * 128, dst + 96 * 128);
      }
      done_slot(s);
    }
    PROF_STAMP(8);
    uint32_t pending = active;
    uint32_t it = 0;
    while (pending) {
      for (int s = 0; s < NS; s++) {
        if (!((pending >> s) & 1u)) continue;
        if (((used >> s) & 1u) && !mbar_test(bar_empty + 8 * s, ((upar >> s) & 1u) ^ 1u)) continue;
        pending &= ~(1u << s);
        post(s, (uint32_t)T_END << 28);
      }
      if (++it > (1u << 24)) __trap();
    }
    return;
  }

  const int g = lane >> 2, j = lane & 3;
  float* xs = reinterpret_cast<float*>(smem + SM_X);
  float* red = reinterpret_cast<float*>(smem + SM_RED);
  uint32_t* vh = reinterpret_cast<uint32_t*>(smem + SM_VH);

  {
    uint32_t bf[10];
    if (has_h1) {
      uint32_t af[5][4];
      vec_frags(reinterpret_cast<const uint32_t*>(smem + SM_VA), warp, lane, bf);
      mbar_wait(bar_full + (warp >= 4 ? 8 : 0), 0);
      if (tid == 0) PROF_STAMP(38);
      slice_frags(sb, warp, lane, af);
      slice_mma(af, bf, red, warp, lane);
      cons_bar();
      if (warp == 0) {
        const float v = red8(red, lane & 15);
        const float vn = __shfl_down_sync(0xffffffffu, v, 1);
        if (!(lane & 1)) {
          const uint32_t w = pack_bf16(v, vn);
          st_relaxed_v2(&g_llmod[(lane >> 4) * 2][h1 * 8 + ((lane & 15) >> 1)], w, ep + 1);
          st_relaxed_v2(&g_llmod[(lane >> 4) * 2 + 1][h1 * 8 + ((lane & 15) >> 1)], w, ep + 1);
        }
        if (lane == 0) { mbar_arrive(bar_empty); PROF_STAMP(7); }
        __syncwarp();
      }
    }
    float mean_b, rstd;
    ln_stats(xs, lane, mean_b, rstd);
    const uint32_t* sc = reinterpret_cast<const uint32_t*>(smem + SM_Q);
    mbar_wait(bar_mod, 0);
    for (int p = tid; p < D_MODEL / 2; p += 256) vh[p] = ln_mod2(xs[2 * p], xs[2 * p + 1], mean_b, rstd, sc[320 + p], sc[p]);
    __syncwarp();
    cons_bar();
    if (tid == 0) PROF_STAMP(29);
    if (has_h3) {
      vec_frags(vh, warp, lane, bf);
      const int sl = has_h1 + (warp >> 1);
      mbar_wait(bar_full + 16 * sl + 8 * (warp & 1), 0);
      if (tid == 0) PROF_STAMP(48);
      const int r0 = (lane & 7) + ((lane >> 4) << 3), lo = (lane >> 3) & 1;
      const uint32_t vg = sb + sl * SLOT_BYTES + ((warp & 1) * 80 + r0) * 128 + ((lo ^ (r0 & 7)) << 4);
      float qa[4][4];
#pragma unroll
      for (int m = 0; m < 4; m++) { qa[m][0] = qa[m][1] = qa[m][2] = qa[m][3] = 0.f; }
#pragma unroll
      for (int ks = 0; ks < 5; ks++) {
#pragma unroll
        for (int m = 0; m < 4; m++) {
          uint32_t a4[4];
          ldsm4t(a4, (vg + ks * 2048) ^ (m << 5));
          mma16816(qa[m], a4, bf[2 * ks], bf[2 * ks + 1]);
        }
      }
      red[(16 * j + g) * 8 + warp] = sel4(j, qa[0][0], qa[1][0], qa[2][0], qa[3][0]);
      red[(16 * j + 8 + g) * 8 + warp] = sel4(j, qa[0][2], qa[1][2], qa[2][2], qa[3][2]);
      cons_bar();
      if (tid < 64) {
        mbar_wait(bar_clear, 0);
        const float v = red8(red, tid);
        const float vn = __shfl_down_sync(0xffffffffu, v, 1);
        if (!(tid & 1)) {
          const uint32_t w = ~pack_bf16(v, vn);
#pragma unroll
          for (int r = 0; r < QRE; r++) st_relaxed(&par->llq[r][cta * 32 + (tid >> 1)], w);
        }
        if (tid < 4) mbar_arrive(bar_empty + 8 * (has_h1 + tid));
        __syncwarp();
        if (tid == 32) red_add_u32(&par->hintH3.v, 1u);
      }
    } else if (tid == 0) {
      mbar_wait(bar_clear, 0);
      red_add_u32(&par->hintH3.v, 1u);
    }
    if (tid == 0) PROF_STAMP(2);
    mbar_wait(bar_q, 0);
    {
      uint32_t pend = 7, it = 0;
      while (pend) {
        uint4 v[3];
#pragma unroll
        for (int i = 0; i < 3; i++)
          if ((pend >> i) & 1u) v[i] = ld_relaxed_v4(reinterpret_cast<const uint4*>(par->llq[cta & (QRE - 1)]) + i * 256 + tid);
#pragma unroll
        for (int i = 0; i < 3; i++)
          if (((pend >> i) & 1u) && v[i].x != 0u && v[i].y != 0u && v[i].z != 0u && v[i].w != 0u) {
            reinterpret_cast<uint4*>(smem + SM_Q)[i * 256 + tid] = make_uint4(~v[i].x, ~v[i].y, ~v[i].z, ~v[i].w);
            pend &= ~(1u << i);
          }
        if (pend) NSLEEP;
        if (++it > (1u << 22)) __trap();
      }
    }
    __syncwarp();
    cons_bar();
    if (tid == 0) {
      if (cta == 0) g_epoch = ep + 1;
      PROF_STAMP(3);
    }
  }

  {
    const uint32_t slot = sb + warp * SLOT_BYTES;
    const uint32_t my_full = bar_full + 16 * warp, my_empty = bar_empty + 8 * warp, my_post = bar_post + 8 * warp;
    uint32_t* stage = reinterpret_cast<uint32_t*>(smem + SM_STAGE + warp * 768);
    uint32_t vk[3], vv[3];
    {
      const int r0 = (lane & 7) + (((lane >> 3) & 1) << 3), hi = lane >> 4;
      const int r1 = (lane & 7) + ((lane >> 4) << 3), lo = (lane >> 3) & 1;
#pragma unroll
      for (int t = 0; t < 3; t++) {
        vk[t] = slot + (3 * r0 + t) * 128 + ((hi ^ ((3 * r0 + t) & 7)) << 4);
        vv[t] = slot + (3 * r1 + t) * 128 + ((lo ^ ((3 * r1 + t) & 7)) << 4);
      }
    }
    uint32_t use = (warp < nh) ? 1 : 0;
    for (;; use++) {
      mbar_wait(my_post, use & 1);
      const uint32_t d = desc[warp];
      const int type = d >> 28, a = (d >> 16) & 0xfff, b = d & 0xffff;
      if (type == T_K) {
        const uint32_t* q32 = reinterpret_cast<const uint32_t*>(smem + SM_Q) + a * (DH / 2);
        float s[4][4];
#pragma unroll
        for (int m = 0; m < 4; m++) { s[m][0] = s[m][1] = s[m][2] = s[m][3] = 0.f; }
        mbar_wait(my_full, use & 1);
        mbar_wait(my_full + 8, use & 1);
#pragma unroll
        for (int ks = 0; ks < 12; ks++) {
          const uint32_t b0 = q32[8 * ks + j], b1 = q32[8 * ks + 4 + j];
#pragma unroll
          for (int m = 0; m < 4; m++) {
            uint32_t af[4];
            ldsm4(af, (vk[ks >> 2] ^ ((ks & 3) << 5)) + m * 6144);
            mma16816(s[m], af, b0, b1);
          }
        }
        __syncwarp();
        if (lane == 0) mbar_arrive(my_empty);
        const float scale = 0.07216878364870323f;
        const float s0 = bf16r(sel4(j, s[0][0], s[1][0], s[2][0], s[3][0])) * scale;
        const float s1 = bf16r(sel4(j, s[0][2], s[1][2], s[2][2], s[3][2])) * scale;
        __nv_bfloat16* st16 = reinterpret_cast<__nv_bfloat16*>(stage);
        st16[16 * j + g] = __float2bfloat16_rn(s0);
        st16[16 * j + 8 + g] = __float2bfloat16_rn(s1);
        __syncwarp();
        const uint32_t pr = stage[lane];
        st_relaxed_v2(&g_sc[a * (SK / 2) + b * 32 + lane], pr, ep + 1);
        const float e0 = bf_lo(pr), e1 = bf_hi(pr);
        const float tmax = warp_max(fmaxf(e0, e1));
        const float tsum = warp_sum(fast_exp(e0 - tmax) + fast_exp(e1 - tmax));
        unsigned old = 0;
        if (lane == 0) {
          asm volatile("st.relaxed.gpu.global.v2.f32 [%0], {%1, %2};" ::"l"(&acc->tstat[a * TPH + b]), "f"(tmax), "f"(tsum) : "memory");
          old = atomicAdd(&acc->cntK[a].v, 1u);
        }
        old = __shfl_sync(0xffffffffu, old, 0);
        if (old == TPH - 1) {
          float4 t0, t1;
          uint32_t it = 0;
          do {
            t0 = ld_relaxed_f4(reinterpret_cast<const float4*>(acc->tstat + a * TPH) + lane);
            t1 = ld_relaxed_f4(reinterpret_cast<const float4*>(acc->tstat + a * TPH) + 32 + lane);
            if (++it > (1u << 22)) __trap();
          } while (t0.y == 0.f || t0.w == 0.f || t1.y == 0.f || t1.w == 0.f);
          __syncwarp();
          const float m = warp_max(fmaxf(fmaxf(t0.x, t0.z), fmaxf(t1.x, t1.z)));
          const float l = warp_sum(t0.y * fast_exp(t0.x - m) + t0.w * fast_exp(t0.z - m) +
                                   t1.y * fast_exp(t1.x - m) + t1.w * fast_exp(t1.z - m));
          if (lane == 0) {
            asm volatile("st.relaxed.gpu.global.v2.f32 [%0], {%1, %2};" ::"l"(&acc->hstat[a]), "f"(m), "f"(1.0f / l) : "memory");
          }
        }
      } else if (type == T_V) {
        {
          float2 hs;
          uint2 sv;
          uint32_t it = 0;
          do {
            hs = ld_relaxed_f2(reinterpret_cast<const float*>(&acc->hstat[a]));
            sv = ld_relaxed_v2(&g_sc[a * (SK / 2) + b * 32 + lane]);
            if (++it > (1u << 22)) __trap();
          } while (hs.y == 0.f || sv.y != ep + 1);
          const uint32_t pr = sv.x;
          stage[lane] = pack_bf16(fast_exp(bf_lo(pr) - hs.x) * hs.y, fast_exp(bf_hi(pr) - hs.x) * hs.y);
        }
        __syncwarp();
        uint32_t pb[8];
#pragma unroll
        for (int i = 0; i < 8; i++) pb[i] = stage[4 * i + j];
        float o[12][4];
#pragma unroll
        for (int m = 0; m < 12; m++) { o[m][0] = o[m][1] = o[m][2] = o[m][3] = 0.f; }
        mbar_wait(my_full, use & 1);
        mbar_wait(my_full + 8, use & 1);
#pragma unroll
        for (int ks = 0; ks < 4; ks++) {
#pragma unroll
          for (int m = 0; m < 12; m++) {
            uint32_t af[4];
            ldsm4t(af, (vv[m >> 2] ^ ((m & 3) << 5)) + ks * 6144);
            mma16816(o[m], af, pb[2 * ks], pb[2 * ks + 1]);
          }
        }
        __syncwarp();
        if (lane == 0) mbar_arrive(my_empty);
        {
          float* sf = reinterpret_cast<float*>(stage);
#pragma unroll
          for (int i = 0; i < 3; i++) {
            sf[16 * (4 * i + j) + g] = sel4(j, o[4 * i][0], o[4 * i + 1][0], o[4 * i + 2][0], o[4 * i + 3][0]);
            sf[16 * (4 * i + j) + 8 + g] = sel4(j, o[4 * i][2], o[4 * i + 1][2], o[4 * i + 2][2], o[4 * i + 3][2]);
          }
          __syncwarp();
          float4* dst = acc->o[a][cta & (ORE - 1)];
          red_add_v4(dst + lane, sf[3 * lane], sf[3 * lane + 1], sf[3 * lane + 2], 1.0f);
          red_add_v4(dst + 32 + lane, sf[96 + 3 * lane], sf[96 + 3 * lane + 1], sf[96 + 3 * lane + 2], 1.0f);
          __syncwarp();
          if (lane == 0) red_add_u32(&acc->hintV[a].v, 1u);
        }
      } else if (type == T_WO || type == T_WF) {
        const int c0 = b * 64 + 16 * j + g;
        const bool last = type == T_WF && a == NH - 1;
        float pre0 = 0.f, pre1 = 0.f;
        uint2 gw0 = make_uint2(0u, 0u), gw1 = make_uint2(0u, 0u);
        if (last) {
          const uint2* gp = &g_llmod[cta & (QRE - 1)][2 * (D_MODEL / 2)];
          uint32_t itg = 0;
          do {
            gw0 = ld_relaxed_v2(gp + (c0 >> 1)); gw1 = ld_relaxed_v2(gp + ((c0 + 8) >> 1));
            if (++itg > (1u << 22)) __trap();
          } while (gw0.y != ep + 1 || gw1.y != ep + 1);
          __syncwarp();
          {
            float2 t0, t1;
            uint32_t it = 0;
            do {
              t0 = ld_relaxed_f2(reinterpret_cast<const float*>(acc->attn + c0));
              t1 = ld_relaxed_f2(reinterpret_cast<const float*>(acc->attn + c0 + 8));
              if (++it > (1u << 22)) __trap();
            } while (t0.y != (float)(NH - NWF) || t1.y != (float)(NH - NWF));
            pre0 = t0.x; pre1 = t1.x;
          }
          __syncwarp();
        }
        {
          float4 u0, u1;
          uint32_t it = 0;
          if (lane == 0) spin_ge(&acc->hintV[a].v, TPH);
          __syncwarp();
          for (;;) {
            float4 t[2][ORE];
#pragma unroll
            for (int r = 0; r < ORE; r++) { t[0][r] = ld_relaxed_f4(&acc->o[a][r][lane]); t[1][r] = ld_relaxed_f4(&acc->o[a][r][32 + lane]); }
            u0 = t[0][0]; u1 = t[1][0];
#pragma unroll
            for (int r = 1; r < ORE; r++) {
              u0.x += t[0][r].x; u0.y += t[0][r].y; u0.z += t[0][r].z; u0.w += t[0][r].w;
              u1.x += t[1][r].x; u1.y += t[1][r].y; u1.z += t[1][r].z; u1.w += t[1][r].w;
            }
            if (__all_sync(0xffffffffu, u0.w == (float)TPH && u1.w == (float)TPH)) break;
            if (++it > (1u << 22)) __trap();
          }
          __nv_bfloat16* s16 = reinterpret_cast<__nv_bfloat16*>(stage);
          s16[3 * lane] = __float2bfloat16_rn(u0.x); s16[3 * lane + 1] = __float2bfloat16_rn(u0.y); s16[3 * lane + 2] = __float2bfloat16_rn(u0.z);
          s16[96 + 3 * lane] = __float2bfloat16_rn(u1.x); s16[96 + 3 * lane + 1] = __float2bfloat16_rn(u1.y); s16[96 + 3 * lane + 2] = __float2bfloat16_rn(u1.z);
        }
        __syncwarp();
        mbar_wait(my_full, use & 1);
        mbar_wait(my_full + 8, use & 1);
        float v0, v1;
        gemv_tile<12>(slot, stage, lane, v0, v1);
        __syncwarp();
        if (lane == 0) mbar_arrive(my_empty);
        if (type == T_WO) {
          red_add_v2(acc->attn + c0, v0, 1.0f);
          red_add_v2(acc->attn + c0 + 8, v1, 1.0f);
          if (lane == 0) PROF_STAMP(14);
        } else if (!last) {
          red[(NH - 1 - a) * 64 + 16 * j + g] = v0; red[(NH - 1 - a) * 64 + 16 * j + 8 + g] = v1;
          __syncwarp();
          if (lane == 0) mbar_arrive(bar_wf);
        } else {
          if (lane == 0) PROF_STAMP(32);
          const float ga0 = (g & 1) ? bf_hi(gw0.x) : bf_lo(gw0.x), ga1 = (g & 1) ? bf_hi(gw1.x) : bf_lo(gw1.x);
          mbar_wait(bar_wf, 0);
          if (lane == 0) PROF_STAMP(33);
#pragma unroll
          for (int w = 1; w < NWF; w++) { pre0 += red[w * 64 + 16 * j + g]; pre1 += red[w * 64 + 16 * j + 8 + g]; }
          const float x0 = bf16r(xs[c0] + bf16r(ga0 * bf16r(pre0 + v0)));
          const float x1 = bf16r(xs[c0 + 8] + bf16r(ga1 * bf16r(pre1 + v1)));
          const float n0 = __shfl_down_sync(0xffffffffu, x0, 4), n1 = __shfl_down_sync(0xffffffffu, x1, 4);
          if (!(g & 1)) {
            const uint32_t w0 = ~pack_bf16(x0, n0), w1 = ~pack_bf16(x1, n1);
#pragma unroll
            for (int r = 0; r < XRE; r++) {
              st_relaxed(&acc->llx1[r][c0 >> 1], w0);
              st_relaxed(&acc->llx1[r][(c0 + 8) >> 1], w1);
            }
          }
        }
      } else if (type == T_MS) {
        const uint32_t* va32 = reinterpret_cast<const uint32_t*>(smem + SM_VA);
        const int r0 = (lane & 7) + ((lane >> 4) << 3), lo = (lane >> 3) & 1;
        const uint32_t w = slot + r0 * 32 + ((lo ^ ((r0 >> 2) & 1)) << 4);
        float ma[4][4];
#pragma unroll
        for (int i = 0; i < 4; i++) { ma[i][0] = ma[i][1] = ma[i][2] = ma[i][3] = 0.f; }
        mbar_wait(my_full, use & 1);
        mbar_wait(my_full + 8, use & 1);
#pragma unroll 2
        for (int k4 = 0; k4 < 10; k4++) {
#pragma unroll
          for (int i = 0; i < 4; i++) {
            uint32_t af[4];
            ldsm4t(af, w + (4 * k4 + i) * 512);
            mma16816(ma[i], af, va32[8 * (4 * k4 + i) + j], va32[8 * (4 * k4 + i) + 4 + j]);
          }
        }
        __syncwarp();
        if (lane == 0) mbar_arrive(my_empty);
        const float v0 = (ma[0][0] + ma[1][0]) + (ma[2][0] + ma[3][0]), v1 = (ma[0][2] + ma[1][2]) + (ma[2][2] + ma[3][2]);
        const float n0 = __shfl_down_sync(0xffffffffu, v0, 4), n1 = __shfl_down_sync(0xffffffffu, v1, 4);
        if (!(g & 1)) {
          st_relaxed_v2(&g_llmod[j][b * 8 + (g >> 1)], pack_bf16(v0, n0), ep + 1);
          st_relaxed_v2(&g_llmod[j][b * 8 + 4 + (g >> 1)], pack_bf16(v1, n1), ep + 1);
        }
        if (lane == 0) PROF_STAMP(b < 120 ? 35 : 39);
      } else {
        break;
      }
    }
  }

  if (tid == 0) PROF_STAMP(9);
  uint32_t f1a[5][4], f1b[5][4], f2a[12][4];
  uint32_t sbp[4] = {0u, 0u, 0u, 0u}, cbp[4] = {0u, 0u, 0u, 0u};
  float gb = 0.f;
  const int gt = tid < 80 ? tid : tid - 16;
  const uint2* modp = g_llmod[cta & (QRE - 1)];
  auto mod_word = [&](int w) {
    uint2 v;
    uint32_t it = 0;
    do {
      v = ld_relaxed_v2(modp + w);
      if (++it > (1u << 22)) __trap();
    } while (v.y != ep + 1);
    return v.x;
  };
  auto tail_wait = [&](int ti, int h) {
    mbar_wait(bar_tail + 8 * ti, 0);
    const uint32_t ts = tailslot[ti];
    mbar_wait(bar_full + 16 * (ts & 7u) + 8 * h, ts >> 8);
    return sb + (ts & 7u) * SLOT_BYTES;
  };
  if (has_f1) {
    if (tid < 96) {
      uint32_t it = 0;
      uint4 s0, s1, c0, c1;
      const unsigned tg = ep + 1;
      do {
        s0 = ld_relaxed_v4(modp + 3 * 320 + 4 * gt); s1 = ld_relaxed_v4(modp + 3 * 320 + 4 * gt + 2);
        c0 = ld_relaxed_v4(modp + 4 * 320 + 4 * gt); c1 = ld_relaxed_v4(modp + 4 * 320 + 4 * gt + 2);
        if (++it > (1u << 22)) __trap();
      } while (s0.y != tg || s0.w != tg || s1.y != tg || s1.w != tg || c0.y != tg || c0.w != tg || c1.y != tg || c1.w != tg);
      sbp[0] = s0.x; sbp[1] = s0.z; sbp[2] = s1.x; sbp[3] = s1.z;
      cbp[0] = pack_bf16(1.0f + bf_lo(c0.x), 1.0f + bf_hi(c0.x)); cbp[1] = pack_bf16(1.0f + bf_lo(c0.z), 1.0f + bf_hi(c0.z));
      cbp[2] = pack_bf16(1.0f + bf_lo(c1.x), 1.0f + bf_hi(c1.x)); cbp[3] = pack_bf16(1.0f + bf_lo(c1.z), 1.0f + bf_hi(c1.z));
    }
    __syncwarp();
    if (tid == 0) PROF_STAMP(34);
    slice_frags(tail_wait(0, warp >= 4), warp, lane, f1a);
    slice_frags(tail_wait(1, warp >= 4), warp, lane, f1b);
  }
  auto f2_preload = [&]() {
    if (tid < (has_f2b ? 32 : 16)) {
      const uint32_t w = mod_word(5 * 320 + (tid < 16 ? f2 : f2b) * 8 + ((tid & 15) >> 1));
      gb = (tid & 1) ? bf_hi(w) : bf_lo(w);
    }
    __syncwarp();
    const int r0 = (lane & 7) + ((lane >> 4) << 3), lo = (lane >> 3) & 1;
    const uint32_t base = tail_wait(2 + (warp >> 2), (warp >> 1) & 1) + ((warp & 3) * 192 + r0) * 32 + ((lo ^ ((r0 >> 2) & 1)) << 4);
#pragma unroll
    for (int ks = 0; ks < 12; ks++) ldsm4t(f2a[ks], base + ks * 512);
  };
  if (has_f2) f2_preload();
  if (tid == 0) PROF_STAMP(20);
  constexpr bool live = true;
  if (tid < 96) {
    uint4 v;
    uint32_t it = 0;
    do {
      v = ld_relaxed_v4(reinterpret_cast<const uint4*>(acc->llx1[cta & (XRE - 1)]) + gt);
      if (++it > (1u << 22)) __trap();
    } while (v.x == 0u || v.y == 0u || v.z == 0u || v.w == 0u);
    __syncwarp();
    if (tid == 0) PROF_STAMP(10);
    float x[8] = {bf_lo(~v.x), bf_hi(~v.x), bf_lo(~v.y), bf_hi(~v.y), bf_lo(~v.z), bf_hi(~v.z), bf_lo(~v.w), bf_hi(~v.w)};
    if (has_f2) {
      float4* xd = reinterpret_cast<float4*>(xs) + 2 * gt;
      xd[0] = make_float4(x[0], x[1], x[2], x[3]);
      xd[1] = make_float4(x[4], x[5], x[6], x[7]);
    }
    if (has_f1) {
      float m = (((x[0] + x[1]) + (x[2] + x[3])) + ((x[4] + x[5]) + (x[6] + x[7]))) * 0.125f;
      float q = 0.f, q2 = 0.f;
#pragma unroll
      for (int e = 0; e < 4; e++) {
        const float d0 = x[e] - m, d1 = x[4 + e] - m;
        q = fmaf(d0, d0, q); q2 = fmaf(d1, d1, q2);
      }
      q += q2;
#pragma unroll
      for (int o = 0; o < 5; o++) {
        const float mo = __shfl_xor_sync(0xffffffffu, m, 1 << o), qo = __shfl_xor_sync(0xffffffffu, q, 1 << o);
        const float d = mo - m;
        m = 0.5f * (m + mo);
        q = fmaf(d * d, (float)(4 << o), q + qo);
      }
      float* stat = red + 384;
      if (lane == 0) { stat[2 * warp] = m; stat[2 * warp + 1] = q; }
      asm volatile("bar.sync 4, 96;" ::: "memory");
      const float m0 = stat[0], q0 = stat[1], m1 = stat[2], q1 = stat[3], m2 = stat[4], qd = stat[5];
      const float mean = (0.4f * (m0 + m1)) + 0.2f * m2;
      const float e0 = m0 - mean, e1 = m1 - mean, e2 = m2 - mean;
      const float var = (q0 + q1 + 0.5f * qd + 256.f * (e0 * e0 + e1 * e1) + 128.f * e2 * e2) * (1.0f / D_MODEL);
      const float mean_b = bf16r(mean);
      float sd, rstd;
      asm("sqrt.approx.ftz.f32 %0, %1;" : "=f"(sd) : "f"(bf16r(bf16r(var) + 1e-5f)));
      asm("rcp.approx.ftz.f32 %0, %1;" : "=f"(rstd) : "f"(bf16r(sd)));
      uint32_t h[4];
#pragma unroll
      for (int e = 0; e < 4; e++) {
        const uint32_t a = pack_bf16(x[2 * e] - mean_b, x[2 * e + 1] - mean_b);
        const uint32_t nn = pack_bf16(bf_lo(a) * rstd, bf_hi(a) * rstd);
        const uint32_t t = pack_bf16(bf_lo(nn) * bf_lo(cbp[e]), bf_hi(nn) * bf_hi(cbp[e]));
        h[e] = pack_bf16(bf_lo(t) + bf_lo(sbp[e]), bf_hi(t) + bf_hi(sbp[e]));
      }
      reinterpret_cast<uint4*>(vh)[gt] = make_uint4(h[0], h[1], h[2], h[3]);
    }
    __syncwarp();
  }
  cons_bar();
  if (live && tid == 0) PROF_STAMP(21);
  if (has_f1) {
    uint32_t bf[10];
    vec_frags(vh, warp, lane, bf);
    slice_mma(f1a, bf, red, warp, lane);
    slice_mma(f1b, bf, red + 128, warp, lane);
    if (live && tid == 0) PROF_STAMP(61);
    cons_bar();
    if (live && tid == 0) PROF_STAMP(62);
    if (warp == 0) {
      const float v = bf16r(red8(red, lane));
      const float up = __shfl_down_sync(0xffffffffu, v, 16);
      const float hh = bf16r(bf16r(silu_f(v)) * up);
      const float hn = __shfl_down_sync(0xffffffffu, hh, 1);
      const uint32_t hw = ~pack_bf16(hh, hn);
      const int wi = lane >> 1;
      if (live && lane < 16 && !(lane & 1)) st_relaxed(&acc->llhh[16 * (cta >> 1) + 4 * (wi & 3) + 2 * (cta & 1) + (wi >> 2)], hw);
      if (live && lane == 0) PROF_STAMP(11);
      __syncwarp();
    }
  }
  if (has_f2) {
    uint4 hv[6];
    {
      uint32_t pend = live ? 0x3f : 0, it = 0;
#pragma unroll
      for (int t = 0; t < 6; t++) hv[t] = make_uint4(0u, 0u, 0u, 0u);
      const uint4* src = reinterpret_cast<const uint4*>(acc->llhh) + 24 * warp + j;
      while (pend) {
#pragma unroll
        for (int t = 0; t < 6; t++)
          if ((pend >> t) & 1u) hv[t] = ld_relaxed_v4(src + 4 * t);
#pragma unroll
        for (int t = 0; t < 6; t++)
          if (hv[t].x != 0u && hv[t].y != 0u && hv[t].z != 0u && hv[t].w != 0u) pend &= ~(1u << t);
        if (++it > (1u << 22)) __trap();
      }
      __syncwarp();
    }
    if (live && tid == 0) PROF_STAMP(12);
    float oa[4][4];
#pragma unroll
    for (int i = 0; i < 4; i++) { oa[i][0] = oa[i][1] = oa[i][2] = oa[i][3] = 0.f; }
#pragma unroll
    for (int t = 0; t < 6; t++) {
      mma16816(oa[(2 * t) & 3], f2a[2 * t], ~hv[t].x, ~hv[t].y);
      mma16816(oa[(2 * t + 1) & 3], f2a[2 * t + 1], ~hv[t].z, ~hv[t].w);
    }
    float* red2 = red + 256;
    if (j == 0) {
      red2[g * 8 + warp] = (oa[0][0] + oa[1][0]) + (oa[2][0] + oa[3][0]);
      red2[(8 + g) * 8 + warp] = (oa[0][2] + oa[1][2]) + (oa[2][2] + oa[3][2]);
    }
    if (has_f2b) {
      const int r0 = (lane & 7) + ((lane >> 4) << 3), lo = (lane >> 3) & 1;
      const uint32_t base = tail_wait(warp >> 2, (warp >> 1) & 1) + ((warp & 3) * 192 + r0) * 32 + ((lo ^ ((r0 >> 2) & 1)) << 4);
#pragma unroll
      for (int i = 0; i < 4; i++) { oa[i][0] = oa[i][1] = oa[i][2] = oa[i][3] = 0.f; }
#pragma unroll
      for (int t = 0; t < 6; t++) {
        uint32_t a0[4], a1[4];
        ldsm4t(a0, base + (2 * t) * 512);
        ldsm4t(a1, base + (2 * t + 1) * 512);
        mma16816(oa[(2 * t) & 3], a0, ~hv[t].x, ~hv[t].y);
        mma16816(oa[(2 * t + 1) & 3], a1, ~hv[t].z, ~hv[t].w);
      }
      if (j == 0) {
        red2[(16 + g) * 8 + warp] = (oa[0][0] + oa[1][0]) + (oa[2][0] + oa[3][0]);
        red2[(24 + g) * 8 + warp] = (oa[0][2] + oa[1][2]) + (oa[2][2] + oa[3][2]);
      }
    }
    cons_bar();
    if (tid < (has_f2b ? 32 : 16)) {
      const int col = (tid < 16 ? f2 : f2b) * 16 + (tid & 15);
      prm.out[col] = __float2bfloat16_rn(xs[col] + bf16r(gb * bf16r(red8(red2, tid))));
    }
    if (live && tid == 0) PROF_STAMP(13);
  }
  if (tid == 0) PROF_SYNC(30);
}

typedef CUresult (*EncodeFn)(CUtensorMap*, CUtensorMapDataType, cuuint32_t, void*, const cuuint64_t*,
                             const cuuint64_t*, const cuuint32_t*, const cuuint32_t*, CUtensorMapInterleave,
                             CUtensorMapSwizzle, CUtensorMapL2promotion, CUtensorMapFloatOOBfill);

void make_map(EncodeFn fn, CUtensorMap* tm, const void* base, int rank, const cuuint64_t* dims,
              const cuuint64_t* strides, const cuuint32_t* box, CUtensorMapSwizzle sw, CUtensorMapL2promotion pr) {
  cuuint32_t es[3] = {1, 1, 1};
  fn(tm, CU_TENSOR_MAP_DATA_TYPE_BFLOAT16, rank, const_cast<void*>(base), dims, strides, box, es,
     CU_TENSOR_MAP_INTERLEAVE_NONE, sw, pr, CU_TENSOR_MAP_FLOAT_OOB_FILL_NONE);
}

}

extern "C" void kernel_launch(void* const* d_in, const int* in_sizes, int n_in, void* d_out, int out_size) {
  (void)in_sizes; (void)n_in; (void)out_size;
  static EncodeFn encode = nullptr;
  static int num_sms = 0;
  if (!encode) {
    void* fn = nullptr;
    cudaDriverEntryPointQueryResult qr;
    cudaGetDriverEntryPoint("cuTensorMapEncodeTiled", &fn, cudaEnableDefault, &qr);
    encode = reinterpret_cast<EncodeFn>(fn);
    cudaDeviceGetAttribute(&num_sms, cudaDevAttrMultiProcessorCount, 0);
    cudaFuncSetAttribute(fused_kernel, cudaFuncAttributeMaxDynamicSharedMemorySize, SM_TOTAL);
  }
  CUtensorMap tmK, tmV, tmWq, tmWmodS, tmWo, tmW1, tmW3, tmW2;
  const CUtensorMapL2promotion P128 = CU_TENSOR_MAP_L2_PROMOTION_L2_128B, P256 = CU_TENSOR_MAP_L2_PROMOTION_L2_256B;
  {
    cuuint64_t dims[2] = {64, (cuuint64_t)NH * SK * 3}, str[1] = {128};
    cuuint32_t box[2] = {64, 96};
    make_map(encode, &tmK, d_in[1], 2, dims, str, box, CU_TENSOR_MAP_SWIZZLE_128B, P256);
    make_map(encode, &tmV, d_in[2], 2, dims, str, box, CU_TENSOR_MAP_SWIZZLE_128B, P256);
  }
  {
    cuuint64_t dims[2] = {NH * DH, D_MODEL}, str[1] = {NH * DH * 2};
    cuuint32_t box[2] = {64, 80};
    make_map(encode, &tmWq, d_in[3], 2, dims, str, box, CU_TENSOR_MAP_SWIZZLE_128B, P128);
  }
  {
    cuuint64_t dims3[3] = {6 * D_MODEL, 64, 10}, str3[2] = {6 * D_MODEL * 2, 64 * 6 * D_MODEL * 2};
    cuuint32_t box3[3] = {16, 64, 5};
    make_map(encode, &tmWmodS, d_in[10], 3, dims3, str3, box3, CU_TENSOR_MAP_SWIZZLE_32B, P128);
  }
  {
    cuuint64_t dims[2] = {D_MODEL, NH * DH}, str[1] = {D_MODEL * 2};
    cuuint32_t box[2] = {64, 96};
    make_map(encode, &tmWo, d_in[4], 2, dims, str, box, CU_TENSOR_MAP_SWIZZLE_128B, P128);
  }
  {
    cuuint64_t dims[3] = {FF, 64, 10}, str[2] = {FF * 2, 64 * FF * 2};
    cuuint32_t box[3] = {16, 64, 5};
    make_map(encode, &tmW1, d_in[6], 3, dims, str, box, CU_TENSOR_MAP_SWIZZLE_32B, P128);
    make_map(encode, &tmW3, d_in[7], 3, dims, str, box, CU_TENSOR_MAP_SWIZZLE_32B, P128);
  }
  {
    cuuint64_t dims[3] = {D_MODEL, 128, 12}, str[2] = {D_MODEL * 2, 128 * D_MODEL * 2};
    cuuint32_t box[3] = {16, 128, 3};
    make_map(encode, &tmW2, d_in[8], 3, dims, str, box, CU_TENSOR_MAP_SWIZZLE_32B, P128);
  }
  Params prm;
  prm.x = (const __nv_bfloat16*)d_in[0];
  prm.c = (const __nv_bfloat16*)d_in[9];
  prm.wmod = (const char*)d_in[10];
  prm.wq = (const char*)d_in[3];
  prm.kc = (const char*)d_in[1];
  prm.wo = (const char*)d_in[4];
  prm.out = (__nv_bfloat16*)d_out;
  fused_kernel<<<num_sms, NTHREADS, SM_TOTAL, cudaStreamPerThread>>>(tmK, tmV, tmWq, tmWmodS, tmWo, tmW1, tmW3, tmW2, prm);
}
```

```cpp
#include <cuda_runtime.h>
#include <cuda_bf16.h>
#include <cuda.h>
#include <stdint.h>

namespace {

constexpr int D_MODEL = 640;
constexpr int NH = 32;
constexpr int SK = 8192;
constexpr int DH = 192;
constexpr int FF = 1536;
constexpr int TPH = 128;
constexpr int NS = 8;
constexpr int SLOT_BYTES = 24576;
constexpr int NCW = 8;
constexpr int W_PROD = NCW, W_JAN = NCW + 1, W_GATH = NCW + 2;
constexpr int NTHREADS = (NCW + 3) * 32;
#define WINDOW 5
#define WIN_HEAD 4
#define WIN_WQ 4
#define KDELAY 0
#define WIN_CATCH 8
#define CATCH_ITEMS 5
#define WIN_TAIL 2
#define WF_LEAD (NWF * 128 + 128 + N_MS)
#define WIN_FFN 3
#define SHALLOW_LEAD 720
#define SMALLW 1
#define WOPF_AHEAD 2
#define TAIL_LEAD 0
#define SLOW_LEAD 0
#define NSTAT 10
constexpr int NSTATIC = NSTAT;
#define PF_CYCLES 1800
#define ORE 4
#define LAG 1
constexpr int QRE = 4;
constexpr int XRE = 4;

constexpr int N_H1 = 80;
constexpr int N_H3 = 96;
constexpr int N_MS = 160;
#define NWF 3
constexpr int N_WO = (NH - NWF) * 10;
constexpr int NK = NH * TPH;
constexpr int NSEQ = NK + NK + N_WO + N_MS;
#define MS_BACK 256
#define N_MSA 40
#define MS_AT (NSEQ - N_MS - MS_BACK)
constexpr int WF_CTA0 = 96;

constexpr int N_F1 = 96;
constexpr int N_F2 = 40;

enum { T_K = 1, T_V = 2, T_WO = 3, T_MS = 4, T_WF = 5, T_END = 15 };

struct __align__(128) Ctr { unsigned v; unsigned pad[31]; };
struct __align__(128) Acc {
  Ctr cntK[NH], hintV[NH];
  float2 tstat[NH * TPH];
  float2 hstat[NH];
  float4 o[NH][ORE][DH / 3];
  float2 attn[D_MODEL];
  uint32_t llx1[XRE][D_MODEL / 2];
  uint32_t llhh[FF / 2];
};
struct __align__(128) Par {
  Ctr ticket, hintH3;
  uint32_t llq[QRE][NH * DH / 2];
};
static_assert(sizeof(Acc) % 16 == 0 && sizeof(Par) % 16 == 0, "");

__device__ Acc g_acc;
__device__ Par g_par[2];
__device__ __align__(128) uint2 g_llmod[QRE][3 * D_MODEL];
__device__ unsigned g_epoch;
__device__ volatile unsigned g_sink;
__device__ __align__(128) uint2 g_sc[NH * SK / 2];

#define PROF_STAMP(i) do {} while (0)
#define PROF_SYNC(i) do {} while (0)

constexpr int SM_SLOTS = 0;
constexpr int SM_STAGE = SM_SLOTS + NS * SLOT_BYTES;
constexpr int SM_Q = SM_STAGE + NCW * 768;
constexpr int SM_VA = SM_Q + NH * DH * 2;
constexpr int SM_VH = SM_VA + D_MODEL * 2;
constexpr int SM_X = SM_VH + D_MODEL * 2;
constexpr int SM_RED = SM_X + D_MODEL * 4;
constexpr int SM_BAR = SM_RED + 64 * 8 * 4;
constexpr int SM_DESC = SM_BAR + 40 * 8;
constexpr int SM_TOTAL = SM_DESC + 64;
static_assert(SM_TOTAL <= 232448, "");

struct Params {
  const __nv_bfloat16* x;
  const __nv_bfloat16* c;
  const char* wmod;
  const char* wq;
  const char* kc;
  const char* wo;
  const char* w1;
  const char* w3;
  const char* w2;
  __nv_bfloat16* out;
};

#define NSLEEP do {} while (0)
__device__ __forceinline__ uint32_t smem_u32(const void* p) { return (uint32_t)__cvta_generic_to_shared(p); }
__device__ __forceinline__ void mbar_init(uint32_t bar, uint32_t cnt) {
  asm volatile("mbarrier.init.shared::cta.b64 [%0], %1;" ::"r"(bar), "r"(cnt) : "memory");
}
__device__ __forceinline__ void mbar_expect_tx(uint32_t bar, uint32_t bytes) {
  asm volatile("mbarrier.arrive.expect_tx.shared::cta.b64 _, [%0], %1;" ::"r"(bar), "r"(bytes) : "memory");
}
__device__ __forceinline__ void mbar_arrive(uint32_t bar) {
  asm volatile("mbarrier.arrive.shared::cta.b64 _, [%0];" ::"r"(bar) : "memory");
}
__device__ __forceinline__ bool mbar_try(uint32_t bar, uint32_t parity) {
  uint32_t ok;
  asm volatile(
      "{\n.reg .pred p;\nmbarrier.try_wait.parity.shared::cta.b64 p, [%1], %2;\nselp.u32 %0, 1, 0, p;\n}"
      : "=r"(ok) : "r"(bar), "r"(parity) : "memory");
  return ok != 0;
}
__device__ __forceinline__ bool mbar_test(uint32_t bar, uint32_t parity) {
  uint32_t ok;
  asm volatile(
      "{\n.reg .pred p;\nmbarrier.test_wait.parity.shared::cta.b64 p, [%1], %2;\nselp.u32 %0, 1, 0, p;\n}"
      : "=r"(ok) : "r"(bar), "r"(parity) : "memory");
  return ok != 0;
}
__device__ __forceinline__ void mbar_wait(uint32_t bar, uint32_t parity) {
  uint32_t it = 0;
  while (!mbar_try(bar, parity)) {
    if (++it > (1u << 24)) __trap();
  }
}
__device__ __forceinline__ void tma_2d(uint32_t dst, const CUtensorMap* tm, int c0, int c1, uint32_t bar, uint64_t pol) {
  asm volatile(
      "cp.async.bulk.tensor.2d.shared::cluster.global.mbarrier::complete_tx::bytes.L2::cache_hint [%0], [%1, {%3, %4}], [%2], %5;"
      ::"r"(dst), "l"(tm), "r"(bar), "r"(c0), "r"(c1), "l"(pol) : "memory");
}
__device__ __forceinline__ void tma_3d(uint32_t dst, const CUtensorMap* tm, int c0, int c1, int c2, uint32_t bar) {
  asm volatile(
      "cp.async.bulk.tensor.3d.shared::cluster.global.mbarrier::complete_tx::bytes [%0], [%1, {%3, %4, %5}], [%2];"
      ::"r"(dst), "l"(tm), "r"(bar), "r"(c0), "r"(c1), "r"(c2) : "memory");
}
__device__ __forceinline__ void prefetch_tm(const CUtensorMap* tm) {
  asm volatile("prefetch.tensormap [%0];" ::"l"(tm) : "memory");
}
__device__ __forceinline__ void ldsm4(uint32_t (&a)[4], uint32_t addr) {
  asm volatile("ldmatrix.sync.aligned.m8n8.x4.shared.b16 {%0,%1,%2,%3}, [%4];"
               : "=r"(a[0]), "=r"(a[1]), "=r"(a[2]), "=r"(a[3]) : "r"(addr) : "memory");
}
__device__ __forceinline__ void ldsm4t(uint32_t (&a)[4], uint32_t addr) {
  asm volatile("ldmatrix.sync.aligned.m8n8.x4.trans.shared.b16 {%0,%1,%2,%3}, [%4];"
               : "=r"(a[0]), "=r"(a[1]), "=r"(a[2]), "=r"(a[3]) : "r"(addr) : "memory");
}
__device__ __forceinline__ void mma16816(float (&d)[4], const uint32_t (&a)[4], uint32_t b0, uint32_t b1) {
  asm volatile(
      "mma.sync.aligned.m16n8k16.row.col.f32.bf16.bf16.f32 {%0,%1,%2,%3}, {%4,%5,%6,%7}, {%8,%9}, {%0,%1,%2,%3};"
      : "+f"(d[0]), "+f"(d[1]), "+f"(d[2]), "+f"(d[3])
      : "r"(a[0]), "r"(a[1]), "r"(a[2]), "r"(a[3]), "r"(b0), "r"(b1));
}
__device__ __forceinline__ unsigned ld_acquire(const unsigned* p) {
  unsigned v;
  asm volatile("ld.acquire.gpu.global.u32 %0, [%1];" : "=r"(v) : "l"(p) : "memory");
  return v;
}
__device__ __forceinline__ unsigned ld_relaxed(const unsigned* p) {
  unsigned v;
  asm volatile("ld.relaxed.gpu.global.u32 %0, [%1];" : "=r"(v) : "l"(p) : "memory");
  return v;
}
__device__ __forceinline__ float2 ld_relaxed_f2(const float* p) {
  float2 v;
  asm volatile("ld.relaxed.gpu.global.v2.f32 {%0,%1}, [%2];" : "=f"(v.x), "=f"(v.y) : "l"(p) : "memory");
  return v;
}
__device__ __forceinline__ float ld_relaxed_f(const float* p) {
  float v;
  asm volatile("ld.relaxed.gpu.global.f32 %0, [%1];" : "=f"(v) : "l"(p) : "memory");
  return v;
}
__device__ __forceinline__ uint2 ld_relaxed_v2(const uint2* p) {
  uint2 v;
  asm volatile("ld.relaxed.gpu.global.v2.u32 {%0,%1}, [%2];" : "=r"(v.x), "=r"(v.y) : "l"(p) : "memory");
  return v;
}
__device__ __forceinline__ uint4 ld_relaxed_v4(const void* p) {
  uint4 v;
  asm volatile("ld.relaxed.gpu.global.v4.u32 {%0,%1,%2,%3}, [%4];" : "=r"(v.x), "=r"(v.y), "=r"(v.z), "=r"(v.w) : "l"(p) : "memory");
  return v;
}
__device__ __forceinline__ void st_relaxed_v2(uint2* p, uint32_t a, uint32_t b) {
  asm volatile("st.relaxed.gpu.global.v2.u32 [%0], {%1, %2};" ::"l"(p), "r"(a), "r"(b) : "memory");
}
__device__ __forceinline__ void st_relaxed(unsigned* p, unsigned v) {
  asm volatile("st.relaxed.gpu.global.u32 [%0], %1;" ::"l"(p), "r"(v) : "memory");
}
__device__ __forceinline__ void fence_gpu() { asm volatile("fence.acq_rel.gpu;" ::: "memory"); }
__device__ __forceinline__ float atom_add_f32(float* p, float v) {
  float r;
  asm volatile("atom.relaxed.gpu.global.add.f32 %0, [%1], %2;" : "=f"(r) : "l"(p), "f"(v) : "memory");
  return r;
}
__device__ __forceinline__ void red_add_v4(float4* p, float a, float b, float c, float d) {
  asm volatile("red.relaxed.gpu.global.add.v4.f32 [%0], {%1, %2, %3, %4};" ::"l"(p), "f"(a), "f"(b), "f"(c), "f"(d) : "memory");
}
__device__ __forceinline__ void red_add_v2(float2* p, float a, float b) {
  asm volatile("red.relaxed.gpu.global.add.v2.f32 [%0], {%1, %2};" ::"l"(p), "f"(a), "f"(b) : "memory");
}
__device__ __forceinline__ float4 ld_relaxed_f4(const float4* p) {
  float4 v;
  asm volatile("ld.relaxed.gpu.global.v4.f32 {%0,%1,%2,%3}, [%4];" : "=f"(v.x), "=f"(v.y), "=f"(v.z), "=f"(v.w) : "l"(p) : "memory");
  return v;
}
__device__ __forceinline__ void red_add_u32(unsigned* p, unsigned v) {
  asm volatile("red.relaxed.gpu.global.add.u32 [%0], %1;" ::"l"(p), "r"(v) : "memory");
}
__device__ __forceinline__ void spin_ge(const unsigned* p, unsigned target) {
  uint32_t it = 0;
  while (ld_relaxed(p) < target) {
    if (++it > (1u << 22)) __trap();
  }
}
__device__ __forceinline__ void spin_ge_sleep(const unsigned* p, unsigned target) {
  uint32_t it = 0;
  while (ld_relaxed(p) < target) {
    NSLEEP;
    if (++it > (1u << 22)) __trap();
  }
}
__device__ __forceinline__ void cons_bar() { asm volatile("bar.sync 1, 256;" ::: "memory"); }

__device__ __forceinline__ uint32_t pack_bf16(float lo, float hi) {
  uint32_t r;
  asm("cvt.rn.bf16x2.f32 %0, %1, %2;" : "=r"(r) : "f"(hi), "f"(lo));
  return r;
}
__device__ __forceinline__ float bf16r(float x) { return __uint_as_float(pack_bf16(0.f, x) & 0xffff0000u); }
__device__ __forceinline__ float bf_lo(uint32_t v) { return __uint_as_float(v << 16); }
__device__ __forceinline__ float bf_hi(uint32_t v) { return __uint_as_float(v & 0xffff0000u); }
__device__ __forceinline__ float warp_sum(float v) {
#pragma unroll
  for (int o = 16; o > 0; o >>= 1) v += __shfl_xor_sync(0xffffffffu, v, o);
  return v;
}
__device__ __forceinline__ float warp_max(float v) {
#pragma unroll
  for (int o = 16; o > 0; o >>= 1) v = fmaxf(v, __shfl_xor_sync(0xffffffffu, v, o));
  return v;
}
__device__ __forceinline__ float fast_exp(float x) {
  float r;
  asm("ex2.approx.ftz.f32 %0, %1;" : "=f"(r) : "f"(x * 1.4426950408889634f));
  return r;
}
__device__ __forceinline__ float silu_f(float x) {
  float r;
  asm("rcp.approx.f32 %0, %1;" : "=f"(r) : "f"(1.0f + fast_exp(-x)));
  return x * r;
}
__device__ __forceinline__ float sel4(int j, float a, float b, float c, float d) {
  float lo = (j & 1) ? b : a, hi = (j & 1) ? d : c;
  return (j & 2) ? hi : lo;
}

__device__ __forceinline__ void signal_after(unsigned* ctr, uint32_t dep, int lane) {
  const unsigned any = __ballot_sync(0xffffffffu, dep == 0x7fc5a5a5u);
  if (any) g_sink = any;
  if (lane == 0) red_add_u32(ctr, 1u);
}

template <int KS>
__device__ __forceinline__ void gemv_tile(uint32_t slot, const uint32_t* vec32, int lane, float& v0, float& v1) {
  const int j = lane & 3;
  const int r0 = (lane & 7) + ((lane >> 4) << 3), lo = (lane >> 3) & 1;
  const uint32_t vg = slot + r0 * 128 + ((lo ^ (r0 & 7)) << 4);
  float acc[3][4][4];
#pragma unroll
  for (int c = 0; c < 3; c++)
#pragma unroll
    for (int m = 0; m < 4; m++) { acc[c][m][0] = acc[c][m][1] = acc[c][m][2] = acc[c][m][3] = 0.f; }
#pragma unroll
  for (int ks = 0; ks < KS; ks++) {
    const uint32_t b0 = vec32[8 * ks + j], b1 = vec32[8 * ks + 4 + j];
#pragma unroll
    for (int m = 0; m < 4; m++) {
      uint32_t a[4];
      ldsm4t(a, (vg + ks * 2048) ^ (m << 5));
      mma16816(acc[ks % 3][m], a, b0, b1);
    }
  }
  float r0v[4], r2v[4];
#pragma unroll
  for (int m = 0; m < 4; m++) {
    r0v[m] = acc[0][m][0] + acc[1][m][0] + acc[2][m][0];
    r2v[m] = acc[0][m][2] + acc[1][m][2] + acc[2][m][2];
  }
  v0 = sel4(j, r0v[0], r0v[1], r0v[2], r0v[3]);
  v1 = sel4(j, r2v[0], r2v[1], r2v[2], r2v[3]);
}

__device__ __forceinline__ void slice_frags(uint32_t slot, int warp, int lane, uint32_t (&af)[5][4]) {
  const int r0 = (lane & 7) + ((lane >> 4) << 3), lo = (lane >> 3) & 1;
  const uint32_t w = slot + (warp * 80 + r0) * 32 + ((lo ^ ((r0 >> 2) & 1)) << 4);
#pragma unroll
  for (int ks = 0; ks < 5; ks++) ldsm4t(af[ks], w + ks * 512);
}
__device__ __forceinline__ void slice_mma(const uint32_t (&af)[5][4], const uint32_t (&b)[10], float* red, int warp, int lane) {
  float a[3][4];
#pragma unroll
  for (int i = 0; i < 3; i++) { a[i][0] = a[i][1] = a[i][2] = a[i][3] = 0.f; }
#pragma unroll
  for (int ks = 0; ks < 5; ks++) mma16816(a[ks % 3], af[ks], b[2 * ks], b[2 * ks + 1]);
  if ((lane & 3) == 0) {
    red[(lane >> 2) * 8 + warp] = a[0][0] + a[1][0] + a[2][0];
    red[(8 + (lane >> 2)) * 8 + warp] = a[0][2] + a[1][2] + a[2][2];
  }
}
__device__ __forceinline__ void vec_frags(const uint32_t* vec32, int warp, int lane, uint32_t (&b)[10]) {
#pragma unroll
  for (int ks = 0; ks < 5; ks++) {
    b[2 * ks] = vec32[40 * warp + 8 * ks + (lane & 3)];
    b[2 * ks + 1] = vec32[40 * warp + 8 * ks + 4 + (lane & 3)];
  }
}
__device__ __forceinline__ float red8(const float* red, int col) {
  const float4 a = *reinterpret_cast<const float4*>(red + col * 8), b = *reinterpret_cast<const float4*>(red + col * 8 + 4);
  return ((a.x + a.y) + (a.z + a.w)) + ((b.x + b.y) + (b.z + b.w));
}

__device__ __forceinline__ void ln_stats(const float* xs, int lane, float& mean_b, float& rstd) {
  const float k0 = xs[0];
  float s1[4] = {0.f, 0.f, 0.f, 0.f}, s2[4] = {0.f, 0.f, 0.f, 0.f};
#pragma unroll
  for (int i = 0; i < 5; i++) {
    const float4 v = reinterpret_cast<const float4*>(xs)[lane + 32 * i];
    const float d0 = v.x - k0, d1 = v.y - k0, d2 = v.z - k0, d3 = v.w - k0;
    s1[0] += d0; s1[1] += d1; s1[2] += d2; s1[3] += d3;
    s2[0] = fmaf(d0, d0, s2[0]); s2[1] = fmaf(d1, d1, s2[1]); s2[2] = fmaf(d2, d2, s2[2]); s2[3] = fmaf(d3, d3, s2[3]);
  }
  float a = (s1[0] + s1[1]) + (s1[2] + s1[3]), b = (s2[0] + s2[1]) + (s2[2] + s2[3]);
#pragma unroll
  for (int o = 16; o > 0; o >>= 1) {
    a += __shfl_xor_sync(0xffffffffu, a, o);
    b += __shfl_xor_sync(0xffffffffu, b, o);
  }
  const float md = a * (1.0f / D_MODEL);
  const float var = fmaxf(fmaf(-md, md, b * (1.0f / D_MODEL)), 0.f);
  mean_b = bf16r(k0 + md);
  float sd;
  asm("sqrt.approx.ftz.f32 %0, %1;" : "=f"(sd) : "f"(bf16r(bf16r(var) + 1e-5f)));
  asm("rcp.approx.ftz.f32 %0, %1;" : "=f"(rstd) : "f"(bf16r(sd)));
}
__device__ __forceinline__ uint32_t ln_mod2(float x0, float x1, float mean_b, float rstd, uint32_t cpair, uint32_t spair) {
  const uint32_t c1 = pack_bf16(1.0f + bf_lo(cpair), 1.0f + bf_hi(cpair));
  const uint32_t a = pack_bf16(x0 - mean_b, x1 - mean_b);
  const uint32_t n = pack_bf16(bf_lo(a) * rstd, bf_hi(a) * rstd);
  const uint32_t t = pack_bf16(bf_lo(n) * bf_lo(c1), bf_hi(n) * bf_hi(c1));
  return pack_bf16(bf_lo(t) + bf_lo(spair), bf_hi(t) + bf_hi(spair));
}

__global__ void __launch_bounds__(NTHREADS, 1)
fused_kernel(const __grid_constant__ CUtensorMap tmK, const __grid_constant__ CUtensorMap tmV,
             const __grid_constant__ CUtensorMap tmWq,
             const __grid_constant__ CUtensorMap tmWmodS,
             const __grid_constant__ CUtensorMap tmWo, const __grid_constant__ CUtensorMap tmW1,
             const __grid_constant__ CUtensorMap tmW3, const __grid_constant__ CUtensorMap tmW2,
             const Params prm) {
  extern __shared__ __align__(1024) unsigned char smem[];
  const uint32_t sb = smem_u32(smem);
  const int tid = threadIdx.x, warp = tid >> 5, lane = tid & 31;
  const int cta = blockIdx.x, G = gridDim.x;
  const uint32_t bar_full = sb + SM_BAR, bar_empty = bar_full + NS * 16, bar_post = bar_empty + NS * 8,
                 bar_tail = bar_post + NS * 8, bar_clear = bar_tail + 32, bar_mod = bar_clear + 8, bar_q = bar_mod + 8,
                 bar_wf = bar_q + 8;
  volatile uint32_t* desc = reinterpret_cast<volatile uint32_t*>(smem + SM_DESC);
  volatile uint32_t* tailslot = desc + 8;
  volatile uint32_t* s_epoch = desc + 12;
  Acc* const acc = &g_acc;
  const int h1 = cta - (G - N_H1);
  const int has_h1 = h1 >= 0 ? 1 : 0;
  const bool has_h3 = cta < N_H3;
  const int nh = has_h1 + (has_h3 ? 4 : 0);
  const bool has_f1 = cta < N_F1;
  const int f2 = G - 1 - cta;
  const bool has_f2 = cta >= N_F1 && f2 < N_F2;
  const int f2b = f2 + (G - N_F1);
  const bool has_f2b = has_f2 && f2b < N_F2;
  const int wf = cta - WF_CTA0;
  const bool has_wf = wf >= 0 && wf < 10;

  if (warp == W_PROD) {
    if (lane == 0) {
      PROF_SYNC(0);
      for (int i = 0; i < NS; i++) {
        mbar_init(bar_full + 16 * i, 1); mbar_init(bar_full + 16 * i + 8, 1);
        mbar_init(bar_empty + 8 * i, 1); mbar_init(bar_post + 8 * i, 1);
      }
      for (int i = 0; i < 7; i++) mbar_init(bar_tail + 8 * i, 1);
      mbar_init(bar_wf, NWF - 1);
      asm volatile("fence.mbarrier_init.release.cluster;" ::: "memory");
      asm volatile("fence.proxy.async.shared::cta;" ::: "memory");
      if (has_h1) {
        mbar_expect_tx(bar_full, 320 * 32);
        tma_3d(sb, &tmWmodS, h1 * 16, 0, 0, bar_full);
        mbar_expect_tx(bar_full + 8, 320 * 32);
        tma_3d(sb + 320 * 32, &tmWmodS, h1 * 16, 0, 5, bar_full + 8);
      }
      prefetch_tm(&tmWq);
      for (int i = 0; i < nh; i++) mbar_arrive(bar_post + 8 * i);
      prefetch_tm(&tmK);
      prefetch_tm(&tmV);
      prefetch_tm(&tmWo);
    }
    __syncwarp();
    asm volatile("bar.arrive 3, 64;" ::: "memory");
    asm volatile("bar.arrive 0, %0;" ::"n"(NTHREADS - 32) : "memory");
  } else if (warp == W_JAN) {
    uint4* z = reinterpret_cast<uint4*>(acc);
    constexpr int NZ = sizeof(Acc) / 16;
    const int per = (NZ + G - 1) / G;
    for (int i = cta * per + lane; i < min(NZ, (cta + 1) * per); i += 32) z[i] = make_uint4(0, 0, 0, 0);
    __syncwarp();
    if (lane == 0) fence_gpu();
    const unsigned e = *reinterpret_cast<volatile unsigned*>(&g_epoch);
    asm volatile("bar.sync 3, 64;" ::: "memory");
    if (lane == 0) { mbar_arrive(bar_clear); PROF_STAMP(4); }
    uint4* nx = reinterpret_cast<uint4*>(&g_par[(e & 1) ^ 1]);
    constexpr int NZP = sizeof(Par) / 16;
    for (int i = cta * 32 + lane; i < NZP; i += G * 32) nx[i] = make_uint4(0, 0, 0, 0);
    return;
  } else if (warp == W_GATH) {
    {
      const char* pa = lane < 3 ? prm.wmod + min(lane * (2 << 20) + h1 * 32 * (h1 >= 0), 6 * D_MODEL * D_MODEL * 2 - 128)
                     : lane < 7 ? prm.wq + min((lane - 3) * (2 << 20), NH * DH * D_MODEL * 2 - 128)
                                : prm.kc + (size_t)(lane - 7) * (2 << 20) + (size_t)(cta & 63) * SLOT_BYTES;
      if (lane < 16) asm volatile("prefetch.global.L2 [%0];" ::"l"(pa));
    }
    const uint4* src = reinterpret_cast<const uint4*>(g_llmod[cta & (QRE - 1)]) + lane;
    uint4 v[10];
#pragma unroll
    for (int i = 0; i < 10; i++) v[i] = ld_relaxed_v4(src + i * 32);
    const unsigned e = *reinterpret_cast<volatile unsigned*>(&g_epoch);
    if (lane == 0) *s_epoch = e;
    __syncwarp();
    asm volatile("bar.sync 0, %0;" ::"n"(NTHREADS - 32) : "memory");
    const unsigned tg = e + 1;
    uint32_t pend = 0x3ff, it = 0;
    for (;;) {
#pragma unroll
      for (int i = 0; i < 10; i++)
        if (((pend >> i) & 1u) && v[i].y == tg && v[i].w == tg) {
          reinterpret_cast<uint2*>(smem + SM_Q)[i * 32 + lane] = make_uint2(v[i].x, v[i].z);
          pend &= ~(1u << i);
        }
      if (!pend) break;
      NSLEEP;
#pragma unroll
      for (int i = 0; i < 10; i++)
        if ((pend >> i) & 1u) v[i] = ld_relaxed_v4(src + i * 32);
      if (++it > (1u << 22)) __trap();
    }
    __syncwarp();
    if (lane == 0) {
      PROF_STAMP(36);
      mbar_arrive(bar_mod);
      const unsigned* hint = &g_par[e & 1].hintH3.v;
      uint32_t it2 = 0;
      while (ld_acquire(hint) < (unsigned)G) {
        NSLEEP;
        if (++it2 > (1u << 22)) __trap();
      }
      PROF_STAMP(37);
      mbar_arrive(bar_q);
    }
    return;
  } else {
    uint32_t* va = reinterpret_cast<uint32_t*>(smem + SM_VA);
    float* xs = reinterpret_cast<float*>(smem + SM_X);
    const int p1 = tid + 256;
    const uint32_t cv0 = __ldg(reinterpret_cast<const uint32_t*>(prm.c) + tid);
    const uint32_t xv0 = __ldg(reinterpret_cast<const uint32_t*>(prm.x) + tid);
    uint32_t cv1 = 0, xv1 = 0;
    if (tid < 64) {
      cv1 = __ldg(reinterpret_cast<const uint32_t*>(prm.c) + p1);
      xv1 = __ldg(reinterpret_cast<const uint32_t*>(prm.x) + p1);
    }
    va[tid] = pack_bf16(silu_f(bf_lo(cv0)), silu_f(bf_hi(cv0)));
    xs[2 * tid] = bf_lo(xv0);
    xs[2 * tid + 1] = bf_hi(xv0);
    if (tid < 64) {
      va[p1] = pack_bf16(silu_f(bf_lo(cv1)), silu_f(bf_hi(cv1)));
      xs[2 * p1] = bf_lo(xv1);
      xs[2 * p1 + 1] = bf_hi(xv1);
    }
  }
  if (warp == W_PROD) {
    if (lane != 0) return;
    uint64_t pol;
    asm volatile("createpolicy.fractional.L2::evict_first.b64 %0, 1.0;" : "=l"(pol));
    uint32_t tkA = 0, tkB = 0;
    unsigned* ticket = nullptr;
    int win = WIN_WQ;
    bool head_phase = true;
    unsigned long long fifo = 0;
    int nfifo = 0;
    auto throttle = [&]() {
      if (nfifo >= win) {
        const uint32_t e = (uint32_t)(fifo >> (7 * (win - 1))) & 127u;
        mbar_wait(bar_full + 8 * (e >> 1), e & 1u);
      }
    };
    auto push = [&](uint32_t idx, uint32_t parity) { fifo = (fifo << 7) | (idx << 1) | parity; nfifo++; };
    uint32_t active = (1u << NS) - 1, used = 0, upar = 0;
    int cur = 0;
    auto acquire = [&]() {
      const int s = cur;
      do { cur = (cur + 1) & (NS - 1); } while (!((active >> cur) & 1u));
      if ((used >> s) & 1u) mbar_wait(bar_empty + 8 * s, ((upar >> s) & 1u) ^ 1u);
      return s;
    };
    auto post = [&](int s, uint32_t d) {
      desc[s] = d;
      mbar_arrive(bar_post + 8 * s);
    };
    auto issue_half = [&](int s, int h, const CUtensorMap* tm, int c0, int c1, uint32_t bytes, uint32_t dst) {
      throttle();
      const uint32_t bar = bar_full + 16 * s + 8 * h;
      mbar_expect_tx(bar, bytes);
      tma_2d(dst, tm, c0, c1, bar, pol);
      push(2 * s + h, (upar >> s) & 1u);
    };
    auto issue_small = [&](int s, int h, const CUtensorMap* tm, int c0, int z, uint32_t bytes) {
      throttle();
      const uint32_t bar = bar_full + 16 * s + 8 * h;
      mbar_expect_tx(bar, bytes);
      tma_3d(sb + s * SLOT_BYTES + h * bytes, tm, c0, 0, z, bar);
#pragma unroll
      for (int i = 0; i < SMALLW; i++) push(2 * s + h, (upar >> s) & 1u);
    };
    auto done_slot = [&](int s) { upar ^= 1u << s; used |= 1u << s; };
    if (has_h1) { acquire(); push(0, 0); push(1, 0); done_slot(0); }
    for (int i = has_h1; i < nh; i++) {
      const int s = acquire();
      issue_half(s, 0, &tmWq, cta * 64, (i - has_h1) * 160, 80 * 128, sb + s * SLOT_BYTES);
      issue_half(s, 1, &tmWq, cta * 64, (i - has_h1) * 160 + 80, 80 * 128, sb + s * SLOT_BYTES + 80 * 128);
      done_slot(s);
    }
    win = WIN_HEAD;
    int istat = 0;
    int wf_left = has_wf ? NWF : 0;
    bool tail_done = false, shallow = false, tailpf_done = false;
    int pf_done = 0, catch_left = 0;
    for (;;) {
      uint32_t seq;
      if (istat < 0) {
        seq = NSEQ;
      } else if (istat < NSTATIC) {
        seq = cta + G * istat;
        istat++;
        if (istat == NSTATIC - 1) {
          mbar_wait(bar_mod, 0);
          ticket = &g_par[*s_epoch & 1].ticket.v;
          tkA = atomicAdd(ticket, 1u);
          tkB = atomicAdd(ticket, 1u);
        }
      } else {
        if (tkA == 0xfffffffeu) tkA = atomicAdd(ticket, 1u);
        seq = tkA == 0xffffffffu ? NSEQ : NSTATIC * G + tkA;
        tkA = tkB;
        if (seq < NSEQ) {
          if (has_wf && seq >= NSEQ - WF_LEAD) {
            tkB = 0xffffffffu;
          } else if (!shallow && seq >= NSEQ - SHALLOW_LEAD) {
            shallow = true;
            tkB = 0xfffffffeu;
          } else if (shallow) {
            tkA = atomicAdd(ticket, 1u);
          } else {
            tkB = atomicAdd(ticket, 1u);
          }
        }
      }
      if (!tail_done && seq >= NSEQ - TAIL_LEAD && (seq < NSEQ || wf_left == 0)) {
        tail_done = true;
        win = WIN_FFN;
        const int nt = has_f1 ? 2 : has_f2b ? 4 : has_f2 ? 2 : 0;
        for (int k = 0; k < nt; k++) {
          const int ti = has_f1 ? k : (k + 2) & 3;
          const int s = acquire();
          active &= ~(1u << s);
          post(s, (uint32_t)T_END << 28);
          tailslot[ti] = s | (((upar >> s) & 1u) << 8);
          mbar_arrive(bar_tail + 8 * ti);
          if (has_f1) {
            issue_small(s, 0, ti == 0 ? &tmW1 : &tmW3, cta * 16, 0, 320 * 32);
            issue_small(s, 1, ti == 0 ? &tmW1 : &tmW3, cta * 16, 5, 320 * 32);
          } else {
            const int c0 = (ti >= 2 ? f2 : f2b) * 16, z = (ti & 1) * 6;
            issue_small(s, 0, &tmW2, c0, z, 384 * 32);
            issue_small(s, 1, &tmW2, c0, z + 3, 384 * 32);
          }
        }
      }
      int type, a, b;
      if (seq >= NSEQ) {
        if (wf_left == 0) break;
        type = T_WF; a = NH - wf_left; b = wf;
        wf_left--;
        istat = -1;
      } else if (seq >= MS_AT && seq < MS_AT + N_MSA) {
        type = T_MS; a = 0; b = N_H1 + (seq - MS_AT);
      } else if (seq >= NSEQ - (N_MS - N_MSA)) {
        type = T_MS; a = 0; b = N_H1 + N_MS - (NSEQ - seq);
      } else if (seq < NK + (MS_AT < NK ? N_MSA : 0)) {
        const uint32_t k = seq < MS_AT ? seq : seq - N_MSA;
        type = T_K; a = k >> 7; b = k & 127;
      } else {
        uint32_t r = seq - NK - (seq >= MS_AT ? N_MSA : 0);
        if (r < LAG * TPH) {
          type = T_V; a = r >> 7; b = r & 127;
        } else {
          r -= LAG * TPH;
          constexpr uint32_t NBLK = NH - NWF;
          const uint32_t blk = r / 138u, off = r - blk * 138u;
          if (blk < NBLK) {
            if (off < TPH) { type = T_V; a = LAG + blk; b = off; }
            else { type = T_WO; a = blk; b = off - TPH; }
          } else {
            r -= NBLK * 138u;
            type = T_V; a = LAG + NBLK + (r >> 7); b = r & 127;
          }
        }
      }
      if (head_phase && ((used >> cur) & 1u)) {
        int pf = istat;
        if (pf < pf_done) pf = pf_done;
        long long t_next = clock64();
        while (pf < NSTATIC && !mbar_test(bar_empty + 8 * cur, ((upar >> cur) & 1u) ^ 1u)) {
          if (clock64() >= t_next) {
            asm volatile("cp.async.bulk.prefetch.L2.global [%0], %1;" ::"l"(prm.kc + (size_t)(cta + G * pf) * SLOT_BYTES), "r"(SLOT_BYTES) : "memory");
            pf++;
            t_next += PF_CYCLES;
          }
        }
        pf_done = pf;
      }
      const int s = acquire();
      post(s, ((uint32_t)type << 28) | (a << 16) | b);
      if (head_phase && mbar_test(bar_q, 0)) { head_phase = false; win = WIN_CATCH; catch_left = CATCH_ITEMS; PROF_STAMP(43); }
      if (catch_left > 0 && --catch_left == 0) win = WINDOW;
      if (seq >= NSEQ - (N_MS - N_MSA) - SLOW_LEAD && type != T_WF && !tail_done) win = WIN_TAIL;
      const uint32_t dst = sb + s * SLOT_BYTES;
      if (type == T_MS) {
        issue_small(s, 0, &tmWmodS, b * 16, 0, 320 * 32);
        issue_small(s, 1, &tmWmodS, b * 16, 5, 320 * 32);
      } else {
        const CUtensorMap* tm = type == T_K ? &tmK : type == T_V ? &tmV : &tmWo;
        const int c0 = (type == T_K || type == T_V) ? 0 : b * 64;
        const int c1 = (type == T_K || type == T_V) ? (a * TPH + b) * 192 : a * DH;
        issue_half(s, 0, tm, c0, c1, 96 * 128, dst);
        issue_half(s, 1, tm, c0, c1 + 96, 96 * 128, dst + 96 * 128);
      }
      done_slot(s);
    }
    PROF_STAMP(8);
    uint32_t pending = active;
    uint32_t it = 0;
    while (pending) {
      for (int s = 0; s < NS; s++) {
        if (!((pending >> s) & 1u)) continue;
        if (((used >> s) & 1u) && !mbar_test(bar_empty + 8 * s, ((upar >> s) & 1u) ^ 1u)) continue;
        pending &= ~(1u << s);
        post(s, (uint32_t)T_END << 28);
      }
      if (++it > (1u << 24)) __trap();
    }
    return;
  }

  asm volatile("bar.sync 0, %0;" ::"n"(NTHREADS - 32) : "memory");
  const unsigned ep = *s_epoch;
  Par* const par = &g_par[ep & 1];

  const int g = lane >> 2, j = lane & 3;
  float* xs = reinterpret_cast<float*>(smem + SM_X);
  float* red = reinterpret_cast<float*>(smem + SM_RED);
  uint32_t* vh = reinterpret_cast<uint32_t*>(smem + SM_VH);

  {
    uint32_t bf[10];
    if (has_h1) {
      uint32_t af[5][4];
      vec_frags(reinterpret_cast<const uint32_t*>(smem + SM_VA), warp, lane, bf);
      mbar_wait(bar_full + (warp >= 4 ? 8 : 0), 0);
      if (tid == 0) PROF_STAMP(38);
      slice_frags(sb, warp, lane, af);
      slice_mma(af, bf, red, warp, lane);
      cons_bar();
      if (warp == 0) {
        const float v = red8(red, lane & 15);
        const float vn = __shfl_down_sync(0xffffffffu, v, 1);
        if (!(lane & 1)) {
          const uint32_t w = pack_bf16(v, vn);
          st_relaxed_v2(&g_llmod[(lane >> 4) * 2][h1 * 8 + ((lane & 15) >> 1)], w, ep + 1);
          st_relaxed_v2(&g_llmod[(lane >> 4) * 2 + 1][h1 * 8 + ((lane & 15) >> 1)], w, ep + 1);
        }
        if (lane == 0) { mbar_arrive(bar_empty); PROF_STAMP(7); }
        __syncwarp();
      }
    }
    float mean_b, rstd;
    ln_stats(xs, lane, mean_b, rstd);
    const uint32_t* sc = reinterpret_cast<const uint32_t*>(smem + SM_Q);
    mbar_wait(bar_mod, 0);
    for (int p = tid; p < D_MODEL / 2; p += 256) vh[p] = ln_mod2(xs[2 * p], xs[2 * p + 1], mean_b, rstd, sc[320 + p], sc[p]);
    __syncwarp();
    cons_bar();
    if (tid == 0) PROF_STAMP(29);
    if (has_h3) {
      vec_frags(vh, warp, lane, bf);
      const int sl = has_h1 + (warp >> 1);
      mbar_wait(bar_full + 16 * sl + 8 * (warp & 1), 0);
      if (tid == 0) PROF_STAMP(48);
      const int r0 = (lane & 7) + ((lane >> 4) << 3), lo = (lane >> 3) & 1;
      const uint32_t vg = sb + sl * SLOT_BYTES + ((warp & 1) * 80 + r0) * 128 + ((lo ^ (r0 & 7)) << 4);
      float qa[4][4];
#pragma unroll
      for (int m = 0; m < 4; m++) { qa[m][0] = qa[m][1] = qa[m][2] = qa[m][3] = 0.f; }
#pragma unroll
      for (int ks = 0; ks < 5; ks++) {
#pragma unroll
        for (int m = 0; m < 4; m++) {
          uint32_t a4[4];
          ldsm4t(a4, (vg + ks * 2048) ^ (m << 5));
          mma16816(qa[m], a4, bf[2 * ks], bf[2 * ks + 1]);
        }
      }
      red[(16 * j + g) * 8 + warp] = sel4(j, qa[0][0], qa[1][0], qa[2][0], qa[3][0]);
      red[(16 * j + 8 + g) * 8 + warp] = sel4(j, qa[0][2], qa[1][2], qa[2][2], qa[3][2]);
      cons_bar();
      if (tid < 64) {
        mbar_wait(bar_clear, 0);
        const float v = red8(red, tid);
        const float vn = __shfl_down_sync(0xffffffffu, v, 1);
        if (!(tid & 1)) {
          const uint32_t w = ~pack_bf16(v, vn);
#pragma unroll
          for (int r = 0; r < QRE; r++) st_relaxed(&par->llq[r][cta * 32 + (tid >> 1)], w);
        }
        if (tid < 4) mbar_arrive(bar_empty + 8 * (has_h1 + tid));
        __syncwarp();
        if (tid == 32) red_add_u32(&par->hintH3.v, 1u);
      }
    } else if (tid == 0) {
      mbar_wait(bar_clear, 0);
      red_add_u32(&par->hintH3.v, 1u);
    }
    if (tid == 0) PROF_STAMP(2);
    mbar_wait(bar_q, 0);
    {
      uint32_t pend = 7, it = 0;
      while (pend) {
        uint4 v[3];
#pragma unroll
        for (int i = 0; i < 3; i++)
          if ((pend >> i) & 1u) v[i] = ld_relaxed_v4(reinterpret_cast<const uint4*>(par->llq[cta & (QRE - 1)]) + i * 256 + tid);
#pragma unroll
        for (int i = 0; i < 3; i++)
          if (((pend >> i) & 1u) && v[i].x != 0u && v[i].y != 0u && v[i].z != 0u && v[i].w != 0u) {
            reinterpret_cast<uint4*>(smem + SM_Q)[i * 256 + tid] = make_uint4(~v[i].x, ~v[i].y, ~v[i].z, ~v[i].w);
            pend &= ~(1u << i);
          }
        if (pend) NSLEEP;
        if (++it > (1u << 22)) __trap();
      }
    }
    __syncwarp();
    cons_bar();
    if (tid == 0) {
      if (cta == 0) g_epoch = ep + 1;
      PROF_STAMP(3);
    }
  }

  {
    const uint32_t slot = sb + warp * SLOT_BYTES;
    const uint32_t my_full = bar_full + 16 * warp, my_empty = bar_empty + 8 * warp, my_post = bar_post + 8 * warp;
    uint32_t* stage = reinterpret_cast<uint32_t*>(smem + SM_STAGE + warp * 768);
    uint32_t vk[3], vv[3];
    {
      const int r0 = (lane & 7) + (((lane >> 3) & 1) << 3), hi = lane >> 4;
      const int r1 = (lane & 7) + ((lane >> 4) << 3), lo = (lane >> 3) & 1;
#pragma unroll
      for (int t = 0; t < 3; t++) {
        vk[t] = slot + (3 * r0 + t) * 128 + ((hi ^ ((3 * r0 + t) & 7)) << 4);
        vv[t] = slot + (3 * r1 + t) * 128 + ((lo ^ ((3 * r1 + t) & 7)) << 4);
      }
    }
    uint32_t use = (warp < nh) ? 1 : 0;
    for (;; use++) {
      mbar_wait(my_post, use & 1);
      const uint32_t d = desc[warp];
      const int type = d >> 28, a = (d >> 16) & 0xfff, b = d & 0xffff;
      if (type == T_K) {
        const uint32_t* q32 = reinterpret_cast<const uint32_t*>(smem + SM_Q) + a * (DH / 2);
        float s[4][4];
#pragma unroll
        for (int m = 0; m < 4; m++) { s[m][0] = s[m][1] = s[m][2] = s[m][3] = 0.f; }
        mbar_wait(my_full, use & 1);
        mbar_wait(my_full + 8, use & 1);
#pragma unroll
        for (int ks = 0; ks < 12; ks++) {
          const uint32_t b0 = q32[8 * ks + j], b1 = q32[8 * ks + 4 + j];
#pragma unroll
          for (int m = 0; m < 4; m++) {
            uint32_t af[4];
            ldsm4(af, (vk[ks >> 2] ^ ((ks & 3) << 5)) + m * 6144);
            mma16816(s[m], af, b0, b1);
          }
        }
        __syncwarp();
        if (lane == 0) mbar_arrive(my_empty);
        const float scale = 0.07216878364870323f;
        const float s0 = bf16r(sel4(j, s[0][0], s[1][0], s[2][0], s[3][0])) * scale;
        const float s1 = bf16r(sel4(j, s[0][2], s[1][2], s[2][2], s[3][2])) * scale;
        __nv_bfloat16* st16 = reinterpret_cast<__nv_bfloat16*>(stage);
        st16[16 * j + g] = __float2bfloat16_rn(s0);
        st16[16 * j + 8 + g] = __float2bfloat16_rn(s1);
        __syncwarp();
        const uint32_t pr = stage[lane];
        st_relaxed_v2(&g_sc[a * (SK / 2) + b * 32 + lane], pr, ep + 1);
        const float e0 = bf_lo(pr), e1 = bf_hi(pr);
        const float tmax = warp_max(fmaxf(e0, e1));
        const float tsum = warp_sum(fast_exp(e0 - tmax) + fast_exp(e1 - tmax));
        unsigned old = 0;
        if (lane == 0) {
          asm volatile("st.relaxed.gpu.global.v2.f32 [%0], {%1, %2};" ::"l"(&acc->tstat[a * TPH + b]), "f"(tmax), "f"(tsum) : "memory");
          old = atomicAdd(&acc->cntK[a].v, 1u);
        }
        old = __shfl_sync(0xffffffffu, old, 0);
        if (old == TPH - 1) {
          float4 t0, t1;
          uint32_t it = 0;
          do {
            t0 = ld_relaxed_f4(reinterpret_cast<const float4*>(acc->tstat + a * TPH) + lane);
            t1 = ld_relaxed_f4(reinterpret_cast<const float4*>(acc->tstat + a * TPH) + 32 + lane);
            if (++it > (1u << 22)) __trap();
          } while (t0.y == 0.f || t0.w == 0.f || t1.y == 0.f || t1.w == 0.f);
          __syncwarp();
          const float m = warp_max(fmaxf(fmaxf(t0.x, t0.z), fmaxf(t1.x, t1.z)));
          const float l = warp_sum(t0.y * fast_exp(t0.x - m) + t0.w * fast_exp(t0.z - m) +
                                   t1.y * fast_exp(t1.x - m) + t1.w * fast_exp(t1.z - m));
          if (lane == 0) {
            asm volatile("st.relaxed.gpu.global.v2.f32 [%0], {%1, %2};" ::"l"(&acc->hstat[a]), "f"(m), "f"(1.0f / l) : "memory");
          }
        }
      } else if (type == T_V) {
        {
          float2 hs;
          uint2 sv;
          uint32_t it = 0;
          do {
            hs = ld_relaxed_f2(reinterpret_cast<const float*>(&acc->hstat[a]));
            sv = ld_relaxed_v2(&g_sc[a * (SK / 2) + b * 32 + lane]);
            if (++it > (1u << 22)) __trap();
          } while (hs.y == 0.f || sv.y != ep + 1);
          const uint32_t pr = sv.x;
          stage[lane] = pack_bf16(fast_exp(bf_lo(pr) - hs.x) * hs.y, fast_exp(bf_hi(pr) - hs.x) * hs.y);
        }
        __syncwarp();
        uint32_t pb[8];
#pragma unroll
        for (int i = 0; i < 8; i++) pb[i] = stage[4 * i + j];
        float o[12][4];
#pragma unroll
        for (int m = 0; m < 12; m++) { o[m][0] = o[m][1] = o[m][2] = o[m][3] = 0.f; }
        mbar_wait(my_full, use & 1);
        mbar_wait(my_full + 8, use & 1);
#pragma unroll
        for (int ks = 0; ks < 4; ks++) {
#pragma unroll
          for (int m = 0; m < 12; m++) {
            uint32_t af[4];
            ldsm4t(af, (vv[m >> 2] ^ ((m & 3) << 5)) + ks * 6144);
            mma16816(o[m], af, pb[2 * ks], pb[2 * ks + 1]);
          }
        }
        __syncwarp();
        if (lane == 0) mbar_arrive(my_empty);
        {
          float* sf = reinterpret_cast<float*>(stage);
#pragma unroll
          for (int i = 0; i < 3; i++) {
            sf[16 * (4 * i + j) + g] = sel4(j, o[4 * i][0], o[4 * i + 1][0], o[4 * i + 2][0], o[4 * i + 3][0]);
            sf[16 * (4 * i + j) + 8 + g] = sel4(j, o[4 * i][2], o[4 * i + 1][2], o[4 * i + 2][2], o[4 * i + 3][2]);
          }
          __syncwarp();
          float4* dst = acc->o[a][cta & (ORE - 1)];
          red_add_v4(dst + lane, sf[3 * lane], sf[3 * lane + 1], sf[3 * lane + 2], 1.0f);
          red_add_v4(dst + 32 + lane, sf[96 + 3 * lane], sf[96 + 3 * lane + 1], sf[96 + 3 * lane + 2], 1.0f);
          __syncwarp();
          if (lane == 0) red_add_u32(&acc->hintV[a].v, 1u);
        }
      } else if (type == T_WO || type == T_WF) {
        const int c0 = b * 64 + 16 * j + g;
        const bool last = type == T_WF && a == NH - 1;
        float pre0 = 0.f, pre1 = 0.f;
        uint2 gw0 = make_uint2(0u, 0u), gw1 = make_uint2(0u, 0u);
        if (last) {
          const uint2* gp = &g_llmod[cta & (QRE - 1)][2 * (D_MODEL / 2)];
          uint32_t itg = 0;
          do {
            gw0 = ld_relaxed_v2(gp + (c0 >> 1)); gw1 = ld_relaxed_v2(gp + ((c0 + 8) >> 1));
            if (++itg > (1u << 22)) __trap();
          } while (gw0.y != ep + 1 || gw1.y != ep + 1);
          __syncwarp();
          {
            float2 t0, t1;
            uint32_t it = 0;
            do {
              t0 = ld_relaxed_f2(reinterpret_cast<const float*>(acc->attn + c0));
              t1 = ld_relaxed_f2(reinterpret_cast<const float*>(acc->attn + c0 + 8));
              if (++it > (1u << 22)) __trap();
            } while (t0.y != (float)(NH - NWF) || t1.y != (float)(NH - NWF));
            pre0 = t0.x; pre1 = t1.x;
          }
          __syncwarp();
        }
        {
          float4 u0, u1;
          uint32_t it = 0;
          if (lane == 0) spin_ge(&acc->hintV[a].v, TPH);
          __syncwarp();
          for (;;) {
            float4 t[2][ORE];
#pragma unroll
            for (int r = 0; r < ORE; r++) { t[0][r] = ld_relaxed_f4(&acc->o[a][r][lane]); t[1][r] = ld_relaxed_f4(&acc->o[a][r][32 + lane]); }
            u0 = t[0][0]; u1 = t[1][0];
#pragma unroll
            for (int r = 1; r < ORE; r++) {
              u0.x += t[0][r].x; u0.y += t[0][r].y; u0.z += t[0][r].z; u0.w += t[0][r].w;
              u1.x += t[1][r].x; u1.y += t[1][r].y; u1.z += t[1][r].z; u1.w += t[1][r].w;
            }
            if (__all_sync(0xffffffffu, u0.w == (float)TPH && u1.w == (float)TPH)) break;
            if (++it > (1u << 22)) __trap();
          }
          __nv_bfloat16* s16 = reinterpret_cast<__nv_bfloat16*>(stage);
          s16[3 * lane] = __float2bfloat16_rn(u0.x); s16[3 * lane + 1] = __float2bfloat16_rn(u0.y); s16[3 * lane + 2] = __float2bfloat16_rn(u0.z);
          s16[96 + 3 * lane] = __float2bfloat16_rn(u1.x); s16[96 + 3 * lane + 1] = __float2bfloat16_rn(u1.y); s16[96 + 3 * lane + 2] = __float2bfloat16_rn(u1.z);
        }
        __syncwarp();
        mbar_wait(my_full, use & 1);
        mbar_wait(my_full + 8, use & 1);
        float v0, v1;
        gemv_tile<12>(slot, stage, lane, v0, v1);
        __syncwarp();
        if (lane == 0) mbar_arrive(my_empty);
        if (type == T_WO) {
          red_add_v2(acc->attn + c0, v0, 1.0f);
          red_add_v2(acc->attn + c0 + 8, v1, 1.0f);
          if (lane == 0) PROF_STAMP(14);
        } else if (!last) {
          red[(NH - 1 - a) * 64 + 16 * j + g] = v0; red[(NH - 1 - a) * 64 + 16 * j + 8 + g] = v1;
          __syncwarp();
          if (lane == 0) mbar_arrive(bar_wf);
        } else {
          if (lane == 0) PROF_STAMP(32);
          const float ga0 = (g & 1) ? bf_hi(gw0.x) : bf_lo(gw0.x), ga1 = (g & 1) ? bf_hi(gw1.x) : bf_lo(gw1.x);
          mbar_wait(bar_wf, 0);
          if (lane == 0) PROF_STAMP(33);
#pragma unroll
          for (int w = 1; w < NWF; w++) { pre0 += red[w * 64 + 16 * j + g]; pre1 += red[w * 64 + 16 * j + 8 + g]; }
          const float x0 = bf16r(xs[c0] + bf16r(ga0 * bf16r(pre0 + v0)));
          const float x1 = bf16r(xs[c0 + 8] + bf16r(ga1 * bf16r(pre1 + v1)));
          const float n0 = __shfl_down_sync(0xffffffffu, x0, 4), n1 = __shfl_down_sync(0xffffffffu, x1, 4);
          if (!(g & 1)) {
            const uint32_t w0 = ~pack_bf16(x0, n0), w1 = ~pack_bf16(x1, n1);
#pragma unroll
            for (int r = 0; r < XRE; r++) {
              st_relaxed(&acc->llx1[r][c0 >> 1], w0);
              st_relaxed(&acc->llx1[r][(c0 + 8) >> 1], w1);
            }
          }
        }
      } else if (type == T_MS) {
        const uint32_t* va32 = reinterpret_cast<const uint32_t*>(smem + SM_VA);
        const int r0 = (lane & 7) + ((lane >> 4) << 3), lo = (lane >> 3) & 1;
        const uint32_t w = slot + r0 * 32 + ((lo ^ ((r0 >> 2) & 1)) << 4);
        float ma[4][4];
#pragma unroll
        for (int i = 0; i < 4; i++) { ma[i][0] = ma[i][1] = ma[i][2] = ma[i][3] = 0.f; }
        mbar_wait(my_full, use & 1);
        mbar_wait(my_full + 8, use & 1);
#pragma unroll 2
        for (int k4 = 0; k4 < 10; k4++) {
#pragma unroll
          for (int i = 0; i < 4; i++) {
            uint32_t af[4];
            ldsm4t(af, w + (4 * k4 + i) * 512);
            mma16816(ma[i], af, va32[8 * (4 * k4 + i) + j], va32[8 * (4 * k4 + i) + 4 + j]);
          }
        }
        __syncwarp();
        if (lane == 0) mbar_arrive(my_empty);
        const float v0 = (ma[0][0] + ma[1][0]) + (ma[2][0] + ma[3][0]), v1 = (ma[0][2] + ma[1][2]) + (ma[2][2] + ma[3][2]);
        const float n0 = __shfl_down_sync(0xffffffffu, v0, 4), n1 = __shfl_down_sync(0xffffffffu, v1, 4);
        if (!(g & 1)) {
          st_relaxed_v2(&g_llmod[j][b * 8 + (g >> 1)], pack_bf16(v0, n0), ep + 1);
          st_relaxed_v2(&g_llmod[j][b * 8 + 4 + (g >> 1)], pack_bf16(v1, n1), ep + 1);
        }
        if (lane == 0) PROF_STAMP(b < 120 ? 35 : 39);
      } else {
        break;
      }
    }
  }

  if (tid == 0) PROF_STAMP(9);
  uint32_t f1a[5][4], f1b[5][4], f2a[12][4];
  uint32_t sbp[4] = {0u, 0u, 0u, 0u}, cbp[4] = {0u, 0u, 0u, 0u};
  float gb = 0.f;
  const int gt = tid < 80 ? tid : tid - 16;
  const uint2* modp = g_llmod[cta & (QRE - 1)];
  auto mod_word = [&](int w) {
    uint2 v;
    uint32_t it = 0;
    do {
      v = ld_relaxed_v2(modp + w);
      if (++it > (1u << 22)) __trap();
    } while (v.y != ep + 1);
    return v.x;
  };
  auto tail_wait = [&](int ti, int h) {
    mbar_wait(bar_tail + 8 * ti, 0);
    const uint32_t ts = tailslot[ti];
    mbar_wait(bar_full + 16 * (ts & 7u) + 8 * h, ts >> 8);
    return sb + (ts & 7u) * SLOT_BYTES;
  };
  if (has_f1) {
    if (tid < 96) {
      uint32_t it = 0;
      uint4 s0, s1, c0, c1;
      const unsigned tg = ep + 1;
      do {
        s0 = ld_relaxed_v4(modp + 3 * 320 + 4 * gt); s1 = ld_relaxed_v4(modp + 3 * 320 + 4 * gt + 2);
        c0 = ld_relaxed_v4(modp + 4 * 320 + 4 * gt); c1 = ld_relaxed_v4(modp + 4 * 320 + 4 * gt + 2);
        if (++it > (1u << 22)) __trap();
      } while (s0.y != tg || s0.w != tg || s1.y != tg || s1.w != tg || c0.y != tg || c0.w != tg || c1.y != tg || c1.w != tg);
      sbp[0] = s0.x; sbp[1] = s0.z; sbp[2] = s1.x; sbp[3] = s1.z;
      cbp[0] = pack_bf16(1.0f + bf_lo(c0.x), 1.0f + bf_hi(c0.x)); cbp[1] = pack_bf16(1.0f + bf_lo(c0.z), 1.0f + bf_hi(c0.z));
      cbp[2] = pack_bf16(1.0f + bf_lo(c1.x), 1.0f + bf_hi(c1.x)); cbp[3] = pack_bf16(1.0f + bf_lo(c1.z), 1.0f + bf_hi(c1.z));
    }
    __syncwarp();
    if (tid == 0) PROF_STAMP(34);
    slice_frags(tail_wait(0, warp >= 4), warp, lane, f1a);
    slice_frags(tail_wait(1, warp >= 4), warp, lane, f1b);
  }
  auto f2_preload = [&]() {
    if (tid < (has_f2b ? 32 : 16)) {
      const uint32_t w = mod_word(5 * 320 + (tid < 16 ? f2 : f2b) * 8 + ((tid & 15) >> 1));
      gb = (tid & 1) ? bf_hi(w) : bf_lo(w);
    }
    __syncwarp();
    const int r0 = (lane & 7) + ((lane >> 4) << 3), lo = (lane >> 3) & 1;
    const uint32_t base = tail_wait(2 + (warp >> 2), (warp >> 1) & 1) + ((warp & 3) * 192 + r0) * 32 + ((lo ^ ((r0 >> 2) & 1)) << 4);
#pragma unroll
    for (int ks = 0; ks < 12; ks++) ldsm4t(f2a[ks], base + ks * 512);
  };
  if (has_f2) f2_preload();
  if (tid == 0) PROF_STAMP(20);
  constexpr bool live = true;
  if (tid < 96) {
    uint4 v;
    uint32_t it = 0;
    do {
      v = ld_relaxed_v4(reinterpret_cast<const uint4*>(acc->llx1[cta & (XRE - 1)]) + gt);
      if (++it > (1u << 22)) __trap();
    } while (v.x == 0u || v.y == 0u || v.z == 0u || v.w == 0u);
    __syncwarp();
    if (tid == 0) PROF_STAMP(10);
    float x[8] = {bf_lo(~v.x), bf_hi(~v.x), bf_lo(~v.y), bf_hi(~v.y), bf_lo(~v.z), bf_hi(~v.z), bf_lo(~v.w), bf_hi(~v.w)};
    if (has_f2) {
      float4* xd = reinterpret_cast<float4*>(xs) + 2 * gt;
      xd[0] = make_float4(x[0], x[1], x[2], x[3]);
      xd[1] = make_float4(x[4], x[5], x[6], x[7]);
    }
    if (has_f1) {
      float m = (((x[0] + x[1]) + (x[2] + x[3])) + ((x[4] + x[5]) + (x[6] + x[7]))) * 0.125f;
      float q = 0.f, q2 = 0.f;
#pragma unroll
      for (int e = 0; e < 4; e++) {
        const float d0 = x[e] - m, d1 = x[4 + e] - m;
        q = fmaf(d0, d0, q); q2 = fmaf(d1, d1, q2);
      }
      q += q2;
#pragma unroll
      for (int o = 0; o < 5; o++) {
        const float mo = __shfl_xor_sync(0xffffffffu, m, 1 << o), qo = __shfl_xor_sync(0xffffffffu, q, 1 << o);
        const float d = mo - m;
        m = 0.5f * (m + mo);
        q = fmaf(d * d, (float)(4 << o), q + qo);
      }
      float* stat = red + 384;
      if (lane == 0) { stat[2 * warp] = m; stat[2 * warp + 1] = q; }
      asm volatile("bar.sync 4, 96;" ::: "memory");
      const float m0 = stat[0], q0 = stat[1], m1 = stat[2], q1 = stat[3], m2 = stat[4], qd = stat[5];
      const float mean = (0.4f * (m0 + m1)) + 0.2f * m2;
      const float e0 = m0 - mean, e1 = m1 - mean, e2 = m2 - mean;
      const float var = (q0 + q1 + 0.5f * qd + 256.f * (e0 * e0 + e1 * e1) + 128.f * e2 * e2) * (1.0f / D_MODEL);
      const float mean_b = bf16r(mean);
      float sd, rstd;
      asm("sqrt.approx.ftz.f32 %0, %1;" : "=f"(sd) : "f"(bf16r(bf16r(var) + 1e-5f)));
      asm("rcp.approx.ftz.f32 %0, %1;" : "=f"(rstd) : "f"(bf16r(sd)));
      uint32_t h[4];
#pragma unroll
      for (int e = 0; e < 4; e++) {
        const uint32_t a = pack_bf16(x[2 * e] - mean_b, x[2 * e + 1] - mean_b);
        const uint32_t nn = pack_bf16(bf_lo(a) * rstd, bf_hi(a) * rstd);
        const uint32_t t = pack_bf16(bf_lo(nn) * bf_lo(cbp[e]), bf_hi(nn) * bf_hi(cbp[e]));
        h[e] = pack_bf16(bf_lo(t) + bf_lo(sbp[e]), bf_hi(t) + bf_hi(sbp[e]));
      }
      reinterpret_cast<uint4*>(vh)[gt] = make_uint4(h[0], h[1], h[2], h[3]);
    }
    __syncwarp();
  }
  cons_bar();
  if (live && tid == 0) PROF_STAMP(21);
  if (has_f1) {
    uint32_t bf[10];
    vec_frags(vh, warp, lane, bf);
    slice_mma(f1a, bf, red, warp, lane);
    slice_mma(f1b, bf, red + 128, warp, lane);
    if (live && tid == 0) PROF_STAMP(61);
    cons_bar();
    if (live && tid == 0) PROF_STAMP(62);
    if (warp == 0) {
      const float v = bf16r(red8(red, lane));
      const float up = __shfl_down_sync(0xffffffffu, v, 16);
      const float hh = bf16r(bf16r(silu_f(v)) * up);
      const float hn = __shfl_down_sync(0xffffffffu, hh, 1);
      const uint32_t hw = ~pack_bf16(hh, hn);
      const int wi = lane >> 1;
      if (live && lane < 16 && !(lane & 1)) st_relaxed(&acc->llhh[16 * (cta >> 1) + 4 * (wi & 3) + 2 * (cta & 1) + (wi >> 2)], hw);
      if (live && lane == 0) PROF_STAMP(11);
      __syncwarp();
    }
  }
  if (has_f2) {
    uint4 hv[6];
    {
      uint32_t pend = live ? 0x3f : 0, it = 0;
#pragma unroll
      for (int t = 0; t < 6; t++) hv[t] = make_uint4(0u, 0u, 0u, 0u);
      const uint4* src = reinterpret_cast<const uint4*>(acc->llhh) + 24 * warp + j;
      while (pend) {
#pragma unroll
        for (int t = 0; t < 6; t++)
          if ((pend >> t) & 1u) hv[t] = ld_relaxed_v4(src + 4 * t);
#pragma unroll
        for (int t = 0; t < 6; t++)
          if (hv[t].x != 0u && hv[t].y != 0u && hv[t].z != 0u && hv[t].w != 0u) pend &= ~(1u << t);
        if (++it > (1u << 22)) __trap();
      }
      __syncwarp();
    }
    if (live && tid == 0) PROF_STAMP(12);
    float oa[4][4];
#pragma unroll
    for (int i = 0; i < 4; i++) { oa[i][0] = oa[i][1] = oa[i][2] = oa[i][3] = 0.f; }
#pragma unroll
    for (int t = 0; t < 6; t++) {
      mma16816(oa[(2 * t) & 3], f2a[2 * t], ~hv[t].x, ~hv[t].y);
      mma16816(oa[(2 * t + 1) & 3], f2a[2 * t + 1], ~hv[t].z, ~hv[t].w);
    }
    float* red2 = red + 256;
    if (j == 0) {
      red2[g * 8 + warp] = (oa[0][0] + oa[1][0]) + (oa[2][0] + oa[3][0]);
      red2[(8 + g) * 8 + warp] = (oa[0][2] + oa[1][2]) + (oa[2][2] + oa[3][2]);
    }
    if (has_f2b) {
      const int r0 = (lane & 7) + ((lane >> 4) << 3), lo = (lane >> 3) & 1;
      const uint32_t base = tail_wait(warp >> 2, (warp >> 1) & 1) + ((warp & 3) * 192 + r0) * 32 + ((lo ^ ((r0 >> 2) & 1)) << 4);
#pragma unroll
      for (int i = 0; i < 4; i++) { oa[i][0] = oa[i][1] = oa[i][2] = oa[i][3] = 0.f; }
#pragma unroll
      for (int t = 0; t < 6; t++) {
        uint32_t a0[4], a1[4];
        ldsm4t(a0, base + (2 * t) * 512);
        ldsm4t(a1, base + (2 * t + 1) * 512);
        mma16816(oa[(2 * t) & 3], a0, ~hv[t].x, ~hv[t].y);
        mma16816(oa[(2 * t + 1) & 3], a1, ~hv[t].z, ~hv[t].w);
      }
      if (j == 0) {
        red2[(16 + g) * 8 + warp] = (oa[0][0] + oa[1][0]) + (oa[2][0] + oa[3][0]);
        red2[(24 + g) * 8 + warp] = (oa[0][2] + oa[1][2]) + (oa[2][2] + oa[3][2]);
      }
    }
    cons_bar();
    if (tid < (has_f2b ? 32 : 16)) {
      const int col = (tid < 16 ? f2 : f2b) * 16 + (tid & 15);
      prm.out[col] = __float2bfloat16_rn(xs[col] + bf16r(gb * bf16r(red8(red2, tid))));
    }
    if (live && tid == 0) PROF_STAMP(13);
  }
  if (tid == 0) PROF_SYNC(30);
}

typedef CUresult (*EncodeFn)(CUtensorMap*, CUtensorMapDataType, cuuint32_t, void*, const cuuint64_t*,
                             const cuuint64_t*, const cuuint32_t*, const cuuint32_t*, CUtensorMapInterleave,
                             CUtensorMapSwizzle, CUtensorMapL2promotion, CUtensorMapFloatOOBfill);

void make_map(EncodeFn fn, CUtensorMap* tm, const void* base, int rank, const cuuint64_t* dims,
              const cuuint64_t* strides, const cuuint32_t* box, CUtensorMapSwizzle sw, CUtensorMapL2promotion pr) {
  cuuint32_t es[3] = {1, 1, 1};
  fn(tm, CU_TENSOR_MAP_DATA_TYPE_BFLOAT16, rank, const_cast<void*>(base), dims, strides, box, es,
     CU_TENSOR_MAP_INTERLEAVE_NONE, sw, pr, CU_TENSOR_MAP_FLOAT_OOB_FILL_NONE);
}

}

extern "C" void kernel_launch(void* const* d_in, const int* in_sizes, int n_in, void* d_out, int out_size) {
  (void)in_sizes; (void)n_in; (void)out_size;
  static EncodeFn encode = nullptr;
  static int num_sms = 0;
  if (!encode) {
    void* fn = nullptr;
    cudaDriverEntryPointQueryResult qr;
    cudaGetDriverEntryPoint("cuTensorMapEncodeTiled", &fn, cudaEnableDefault, &qr);
    encode = reinterpret_cast<EncodeFn>(fn);
    cudaDeviceGetAttribute(&num_sms, cudaDevAttrMultiProcessorCount, 0);
    cudaFuncSetAttribute(fused_kernel, cudaFuncAttributeMaxDynamicSharedMemorySize, SM_TOTAL);
  }
  CUtensorMap tmK, tmV, tmWq, tmWmodS, tmWo, tmW1, tmW3, tmW2;
#define PSMALL CU_TENSOR_MAP_L2_PROMOTION_L2_128B
#define PKV CU_TENSOR_MAP_L2_PROMOTION_NONE
  const CUtensorMapL2promotion P128 = CU_TENSOR_MAP_L2_PROMOTION_L2_128B, P256 = PKV, PS = PSMALL;
  {
    cuuint64_t dims[2] = {64, (cuuint64_t)NH * SK * 3}, str[1] = {128};
    cuuint32_t box[2] = {64, 96};
    make_map(encode, &tmK, d_in[1], 2, dims, str, box, CU_TENSOR_MAP_SWIZZLE_128B, P256);
    make_map(encode, &tmV, d_in[2], 2, dims, str, box, CU_TENSOR_MAP_SWIZZLE_128B, P256);
  }
  {
    cuuint64_t dims[2] = {NH * DH, D_MODEL}, str[1] = {NH * DH * 2};
    cuuint32_t box[2] = {64, 80};
    make_map(encode, &tmWq, d_in[3], 2, dims, str, box, CU_TENSOR_MAP_SWIZZLE_128B, P128);
  }
  {
    cuuint64_t dims3[3] = {6 * D_MODEL, 64, 10}, str3[2] = {6 * D_MODEL * 2, 64 * 6 * D_MODEL * 2};
    cuuint32_t box3[3] = {16, 64, 5};
    make_map(encode, &tmWmodS, d_in[10], 3, dims3, str3, box3, CU_TENSOR_MAP_SWIZZLE_32B, PS);
  }
  {
    cuuint64_t dims[2] = {D_MODEL, NH * DH}, str[1] = {D_MODEL * 2};
    cuuint32_t box[2] = {64, 96};
    make_map(encode, &tmWo, d_in[4], 2, dims, str, box, CU_TENSOR_MAP_SWIZZLE_128B, P128);
  }
  {
    cuuint64_t dims[3] = {FF, 64, 10}, str[2] = {FF * 2, 64 * FF * 2};
    cuuint32_t box[3] = {16, 64, 5};
    make_map(encode, &tmW1, d_in[6], 3, dims, str, box, CU_TENSOR_MAP_SWIZZLE_32B, PS);
    make_map(encode, &tmW3, d_in[7], 3, dims, str, box, CU_TENSOR_MAP_SWIZZLE_32B, PS);
  }
  {
    cuuint64_t dims[3] = {D_MODEL, 128, 12}, str[2] = {D_MODEL * 2, 128 * D_MODEL * 2};
    cuuint32_t box[3] = {16, 128, 3};
    make_map(encode, &tmW2, d_in[8], 3, dims, str, box, CU_TENSOR_MAP_SWIZZLE_32B, PS);
  }
  Params prm;
  prm.x = (const __nv_bfloat16*)d_in[0];
  prm.c = (const __nv_bfloat16*)d_in[9];
  prm.wmod = (const char*)d_in[10];
  prm.wq = (const char*)d_in[3];
  prm.kc = (const char*)d_in[1];
  prm.wo = (const char*)d_in[4];
  prm.w1 = (const char*)d_in[6];
  prm.w3 = (const char*)d_in[7];
  prm.w2 = (const char*)d_in[8];
  prm.out = (__nv_bfloat16*)d_out;
  fused_kernel<<<num_sms, NTHREADS, SM_TOTAL, cudaStreamPerThread>>>(tmK, tmV, tmWq, tmWmodS, tmWo, tmW1, tmW3, tmW2, prm);
}
```

```cpp
#include <cuda_runtime.h>
#include <cuda_bf16.h>
#include <cuda.h>
#include <stdint.h>

namespace {

constexpr int D_MODEL = 640;
constexpr int NH = 32;
constexpr int SK = 8192;
constexpr int DH = 192;
constexpr int FF = 1536;
constexpr int TPH = 128;
constexpr int NS = 8;
constexpr int SLOT_BYTES = 24576;
constexpr int NCW = 8;
constexpr int W_PROD = NCW, W_JAN = NCW + 1, W_GATH = NCW + 2;
constexpr int NTHREADS = (NCW + 3) * 32;

constexpr int WINDOW = 5;
constexpr int WIN_HEAD = 4;
constexpr int WIN_CATCH = 8;
constexpr int CATCH_ITEMS = 5;
constexpr int WIN_MS = 4;
constexpr int WIN_FFN = 3;
constexpr int NSTATIC = 10;
constexpr int PF_CYCLES = 1800;
constexpr int ORE = 4;
constexpr int QRE = 4;
constexpr int XRE = 4;

constexpr int N_H1 = 80;
constexpr int N_H3 = 96;
constexpr int N_MS = 160;
constexpr int N_MSA = 40;
constexpr int MS_BACK = 256;
constexpr int NWF = 3;
constexpr int LAG = 1;
constexpr int N_WO = (NH - NWF) * 10;
constexpr int NK = NH * TPH;
constexpr int NSEQ = NK + NK + N_WO + N_MS;
constexpr int MS_AT = NSEQ - N_MS - MS_BACK;
constexpr int WF_LEAD = NWF * 128 + 128 + N_MS;
constexpr int SHALLOW_LEAD = 720;
constexpr int WF_CTA0 = 96;

constexpr int N_F1 = 96;
constexpr int N_F2 = 40;
constexpr int MIN_CTAS = 116, MAX_CTAS = 132;

enum { T_K = 1, T_V = 2, T_WO = 3, T_MS = 4, T_WF = 5, T_END = 15 };

struct __align__(128) Ctr { unsigned v; unsigned pad[31]; };
struct __align__(128) Acc {
  Ctr cntK[NH], hintV[NH];
  float2 tstat[NH * TPH];
  float2 hstat[NH];
  float4 o[NH][ORE][DH / 3];
  float2 attn[D_MODEL];
  uint32_t llx1[XRE][D_MODEL / 2];
  uint32_t llhh[FF / 2];
};
struct __align__(128) Par {
  Ctr ticket, hintH3;
  uint32_t llq[QRE][NH * DH / 2];
};
static_assert(sizeof(Acc) % 16 == 0 && sizeof(Par) % 16 == 0, "");

__device__ Acc g_acc;
__device__ Par g_par[2];
__device__ __align__(128) uint2 g_llmod[QRE][3 * D_MODEL];
__device__ unsigned g_epoch;
__device__ __align__(128) uint2 g_sc[NH * SK / 2];

constexpr int SM_SLOTS = 0;
constexpr int SM_STAGE = SM_SLOTS + NS * SLOT_BYTES;
constexpr int SM_Q = SM_STAGE + NCW * 768;
constexpr int SM_VA = SM_Q + NH * DH * 2;
constexpr int SM_VH = SM_VA + D_MODEL * 2;
constexpr int SM_X = SM_VH + D_MODEL * 2;
constexpr int SM_RED = SM_X + D_MODEL * 4;
constexpr int SM_BAR = SM_RED + 64 * 8 * 4;
constexpr int SM_DESC = SM_BAR + 40 * 8;
constexpr int SM_TOTAL = SM_DESC + 64;
static_assert(SM_TOTAL <= 232448, "");

struct Params {
  const __nv_bfloat16* x;
  const __nv_bfloat16* c;
  const char* wmod;
  const char* wq;
  const char* kc;
  __nv_bfloat16* out;
};

__device__ __forceinline__ uint32_t smem_u32(const void* p) { return (uint32_t)__cvta_generic_to_shared(p); }
__device__ __forceinline__ void mbar_init(uint32_t bar, uint32_t cnt) {
  asm volatile("mbarrier.init.shared::cta.b64 [%0], %1;" ::"r"(bar), "r"(cnt) : "memory");
}
__device__ __forceinline__ void mbar_expect_tx(uint32_t bar, uint32_t bytes) {
  asm volatile("mbarrier.arrive.expect_tx.shared::cta.b64 _, [%0], %1;" ::"r"(bar), "r"(bytes) : "memory");
}
__device__ __forceinline__ void mbar_arrive(uint32_t bar) {
  asm volatile("mbarrier.arrive.shared::cta.b64 _, [%0];" ::"r"(bar) : "memory");
}
__device__ __forceinline__ bool mbar_try(uint32_t bar, uint32_t parity) {
  uint32_t ok;
  asm volatile(
      "{\n.reg .pred p;\nmbarrier.try_wait.parity.shared::cta.b64 p, [%1], %2;\nselp.u32 %0, 1, 0, p;\n}"
      : "=r"(ok) : "r"(bar), "r"(parity) : "memory");
  return ok != 0;
}
__device__ __forceinline__ bool mbar_test(uint32_t bar, uint32_t parity) {
  uint32_t ok;
  asm volatile(
      "{\n.reg .pred p;\nmbarrier.test_wait.parity.shared::cta.b64 p, [%1], %2;\nselp.u32 %0, 1, 0, p;\n}"
      : "=r"(ok) : "r"(bar), "r"(parity) : "memory");
  return ok != 0;
}
__device__ __forceinline__ void mbar_wait(uint32_t bar, uint32_t parity) {
  uint32_t it = 0;
  while (!mbar_try(bar, parity)) {
    if (++it > (1u << 24)) __trap();
  }
}
__device__ __forceinline__ void tma_2d(uint32_t dst, const CUtensorMap* tm, int c0, int c1, uint32_t bar, uint64_t pol) {
  asm volatile(
      "cp.async.bulk.tensor.2d.shared::cluster.global.mbarrier::complete_tx::bytes.L2::cache_hint [%0], [%1, {%3, %4}], [%2], %5;"
      ::"r"(dst), "l"(tm), "r"(bar), "r"(c0), "r"(c1), "l"(pol) : "memory");
}
__device__ __forceinline__ void tma_3d(uint32_t dst, const CUtensorMap* tm, int c0, int c1, int c2, uint32_t bar) {
  asm volatile(
      "cp.async.bulk.tensor.3d.shared::cluster.global.mbarrier::complete_tx::bytes [%0], [%1, {%3, %4, %5}], [%2];"
      ::"r"(dst), "l"(tm), "r"(bar), "r"(c0), "r"(c1), "r"(c2) : "memory");
}
__device__ __forceinline__ void prefetch_tm(const CUtensorMap* tm) {
  asm volatile("prefetch.tensormap [%0];" ::"l"(tm) : "memory");
}
__device__ __forceinline__ void ldsm4(uint32_t (&a)[4], uint32_t addr) {
  asm volatile("ldmatrix.sync.aligned.m8n8.x4.shared.b16 {%0,%1,%2,%3}, [%4];"
               : "=r"(a[0]), "=r"(a[1]), "=r"(a[2]), "=r"(a[3]) : "r"(addr) : "memory");
}
__device__ __forceinline__ void ldsm4t(uint32_t (&a)[4], uint32_t addr) {
  asm volatile("ldmatrix.sync.aligned.m8n8.x4.trans.shared.b16 {%0,%1,%2,%3}, [%4];"
               : "=r"(a[0]), "=r"(a[1]), "=r"(a[2]), "=r"(a[3]) : "r"(addr) : "memory");
}
__device__ __forceinline__ void mma16816(float (&d)[4], const uint32_t (&a)[4], uint32_t b0, uint32_t b1) {
  asm volatile(
      "mma.sync.aligned.m16n8k16.row.col.f32.bf16.bf16.f32 {%0,%1,%2,%3}, {%4,%5,%6,%7}, {%8,%9}, {%0,%1,%2,%3};"
      : "+f"(d[0]), "+f"(d[1]), "+f"(d[2]), "+f"(d[3])
      : "r"(a[0]), "r"(a[1]), "r"(a[2]), "r"(a[3]), "r"(b0), "r"(b1));
}
__device__ __forceinline__ unsigned ld_acquire(const unsigned* p) {
  unsigned v;
  asm volatile("ld.acquire.gpu.global.u32 %0, [%1];" : "=r"(v) : "l"(p) : "memory");
  return v;
}
__device__ __forceinline__ unsigned ld_relaxed(const unsigned* p) {
  unsigned v;
  asm volatile("ld.relaxed.gpu.global.u32 %0, [%1];" : "=r"(v) : "l"(p) : "memory");
  return v;
}
__device__ __forceinline__ float2 ld_relaxed_f2(const float* p) {
  unsigned long long v;
  asm volatile("ld.relaxed.gpu.global.u64 %0, [%1];" : "=l"(v) : "l"(p) : "memory");
  return make_float2(__uint_as_float((uint32_t)v), __uint_as_float((uint32_t)(v >> 32)));
}
__device__ __forceinline__ void st_relaxed_f2(float2* p, float a, float b) {
  const unsigned long long v = ((unsigned long long)__float_as_uint(b) << 32) | __float_as_uint(a);
  asm volatile("st.relaxed.gpu.global.u64 [%0], %1;" ::"l"(p), "l"(v) : "memory");
}
__device__ __forceinline__ uint2 ld_relaxed_v2(const uint2* p) {
  unsigned long long v;
  asm volatile("ld.relaxed.gpu.global.u64 %0, [%1];" : "=l"(v) : "l"(p) : "memory");
  return make_uint2((uint32_t)v, (uint32_t)(v >> 32));
}
__device__ __forceinline__ uint4 ld_relaxed_2x8(const void* p) {
  unsigned long long a, b;
  asm volatile("ld.relaxed.gpu.global.v2.u64 {%0,%1}, [%2];" : "=l"(a), "=l"(b) : "l"(p) : "memory");
  return make_uint4((uint32_t)a, (uint32_t)(a >> 32), (uint32_t)b, (uint32_t)(b >> 32));
}
__device__ __forceinline__ uint4 ld_relaxed_v4(const void* p) {
  uint4 v;
  asm volatile("ld.relaxed.gpu.global.v4.u32 {%0,%1,%2,%3}, [%4];" : "=r"(v.x), "=r"(v.y), "=r"(v.z), "=r"(v.w) : "l"(p) : "memory");
  return v;
}
__device__ __forceinline__ void st_relaxed_v2(uint2* p, uint32_t a, uint32_t b) {
  const unsigned long long v = ((unsigned long long)b << 32) | a;
  asm volatile("st.relaxed.gpu.global.u64 [%0], %1;" ::"l"(p), "l"(v) : "memory");
}
__device__ __forceinline__ void st_relaxed(unsigned* p, unsigned v) {
  asm volatile("st.relaxed.gpu.global.u32 [%0], %1;" ::"l"(p), "r"(v) : "memory");
}
__device__ __forceinline__ void fence_gpu() { asm volatile("fence.acq_rel.gpu;" ::: "memory"); }
__device__ __forceinline__ void red_add_v4(float4* p, float a, float b, float c, float d) {
  asm volatile("red.relaxed.gpu.global.add.v4.f32 [%0], {%1, %2, %3, %4};" ::"l"(p), "f"(a), "f"(b), "f"(c), "f"(d) : "memory");
}
__device__ __forceinline__ void red_add_v2(float2* p, float a, float b) {
  asm volatile("red.relaxed.gpu.global.add.v2.f32 [%0], {%1, %2};" ::"l"(p), "f"(a), "f"(b) : "memory");
}
__device__ __forceinline__ float4 ld_relaxed_f4(const float4* p) {
  float4 v;
  asm volatile("ld.relaxed.gpu.global.v4.f32 {%0,%1,%2,%3}, [%4];" : "=f"(v.x), "=f"(v.y), "=f"(v.z), "=f"(v.w) : "l"(p) : "memory");
  return v;
}
__device__ __forceinline__ void red_add_u32(unsigned* p, unsigned v) {
  asm volatile("red.relaxed.gpu.global.add.u32 [%0], %1;" ::"l"(p), "r"(v) : "memory");
}
__device__ __forceinline__ void spin_ge(const unsigned* p, unsigned target) {
  uint32_t it = 0;
  while (ld_relaxed(p) < target) {
    if (++it > (1u << 22)) __trap();
  }
}
__device__ __forceinline__ void cons_bar() { asm volatile("bar.sync 1, 256;" ::: "memory"); }

__device__ __forceinline__ uint32_t pack_bf16(float lo, float hi) {
  uint32_t r;
  asm("cvt.rn.bf16x2.f32 %0, %1, %2;" : "=r"(r) : "f"(hi), "f"(lo));
  return r;
}
__device__ __forceinline__ float bf16r(float x) { return __uint_as_float(pack_bf16(0.f, x) & 0xffff0000u); }
__device__ __forceinline__ float bf_lo(uint32_t v) { return __uint_as_float(v << 16); }
__device__ __forceinline__ float bf_hi(uint32_t v) { return __uint_as_float(v & 0xffff0000u); }
__device__ __forceinline__ float warp_sum(float v) {
#pragma unroll
  for (int o = 16; o > 0; o >>= 1) v += __shfl_xor_sync(0xffffffffu, v, o);
  return v;
}
__device__ __forceinline__ float warp_max(float v) {
#pragma unroll
  for (int o = 16; o > 0; o >>= 1) v = fmaxf(v, __shfl_xor_sync(0xffffffffu, v, o));
  return v;
}
__device__ __forceinline__ float fast_exp(float x) {
  float r;
  asm("ex2.approx.ftz.f32 %0, %1;" : "=f"(r) : "f"(x * 1.4426950408889634f));
  return r;
}
__device__ __forceinline__ float silu_f(float x) {
  float r;
  asm("rcp.approx.f32 %0, %1;" : "=f"(r) : "f"(1.0f + fast_exp(-x)));
  return x * r;
}
__device__ __forceinline__ float sel4(int j, float a, float b, float c, float d) {
  float lo = (j & 1) ? b : a, hi = (j & 1) ? d : c;
  return (j & 2) ? hi : lo;
}

template <int KS>
__device__ __forceinline__ void gemv_tile(uint32_t slot, const uint32_t* vec32, int lane, float& v0, float& v1) {
  const int j = lane & 3;
  const int r0 = (lane & 7) + ((lane >> 4) << 3), lo = (lane >> 3) & 1;
  const uint32_t vg = slot + r0 * 128 + ((lo ^ (r0 & 7)) << 4);
  float acc[3][4][4];
#pragma unroll
  for (int c = 0; c < 3; c++)
#pragma unroll
    for (int m = 0; m < 4; m++) { acc[c][m][0] = acc[c][m][1] = acc[c][m][2] = acc[c][m][3] = 0.f; }
#pragma unroll
  for (int ks = 0; ks < KS; ks++) {
    const uint32_t b0 = vec32[8 * ks + j], b1 = vec32[8 * ks + 4 + j];
#pragma unroll
    for (int m = 0; m < 4; m++) {
      uint32_t a[4];
      ldsm4t(a, (vg + ks * 2048) ^ (m << 5));
      mma16816(acc[ks % 3][m], a, b0, b1);
    }
  }
  float r0v[4], r2v[4];
#pragma unroll
  for (int m = 0; m < 4; m++) {
    r0v[m] = acc[0][m][0] + acc[1][m][0] + acc[2][m][0];
    r2v[m] = acc[0][m][2] + acc[1][m][2] + acc[2][m][2];
  }
  v0 = sel4(j, r0v[0], r0v[1], r0v[2], r0v[3]);
  v1 = sel4(j, r2v[0], r2v[1], r2v[2], r2v[3]);
}

__device__ __forceinline__ void slice_frags(uint32_t slot, int warp, int lane, uint32_t (&af)[5][4]) {
  const int r0 = (lane & 7) + ((lane >> 4) << 3), lo = (lane >> 3) & 1;
  const uint32_t w = slot + (warp * 80 + r0) * 32 + ((lo ^ ((r0 >> 2) & 1)) << 4);
#pragma unroll
  for (int ks = 0; ks < 5; ks++) ldsm4t(af[ks], w + ks * 512);
}
__device__ __forceinline__ void slice_mma(const uint32_t (&af)[5][4], const uint32_t (&b)[10], float* red, int warp, int lane) {
  float a[3][4];
#pragma unroll
  for (int i = 0; i < 3; i++) { a[i][0] = a[i][1] = a[i][2] = a[i][3] = 0.f; }
#pragma unroll
  for (int ks = 0; ks < 5; ks++) mma16816(a[ks % 3], af[ks], b[2 * ks], b[2 * ks + 1]);
  if ((lane & 3) == 0) {
    red[(lane >> 2) * 8 + warp] = a[0][0] + a[1][0] + a[2][0];
    red[(8 + (lane >> 2)) * 8 + warp] = a[0][2] + a[1][2] + a[2][2];
  }
}
__device__ __forceinline__ void vec_frags(const uint32_t* vec32, int warp, int lane, uint32_t (&b)[10]) {
#pragma unroll
  for (int ks = 0; ks < 5; ks++) {
    b[2 * ks] = vec32[40 * warp + 8 * ks + (lane & 3)];
    b[2 * ks + 1] = vec32[40 * warp + 8 * ks + 4 + (lane & 3)];
  }
}
__device__ __forceinline__ float red8(const float* red, int col) {
  const float4 a = *reinterpret_cast<const float4*>(red + col * 8), b = *reinterpret_cast<const float4*>(red + col * 8 + 4);
  return ((a.x + a.y) + (a.z + a.w)) + ((b.x + b.y) + (b.z + b.w));
}

__device__ __forceinline__ void ln_stats(const float* xs, int lane, float& mean_b, float& rstd) {
  const float k0 = xs[0];
  float s1[4] = {0.f, 0.f, 0.f, 0.f}, s2[4] = {0.f, 0.f, 0.f, 0.f};
#pragma unroll
  for (int i = 0; i < 5; i++) {
    const float4 v = reinterpret_cast<const float4*>(xs)[lane + 32 * i];
    const float d0 = v.x - k0, d1 = v.y - k0, d2 = v.z - k0, d3 = v.w - k0;
    s1[0] += d0; s1[1] += d1; s1[2] += d2; s1[3] += d3;
    s2[0] = fmaf(d0, d0, s2[0]); s2[1] = fmaf(d1, d1, s2[1]); s2[2] = fmaf(d2, d2, s2[2]); s2[3] = fmaf(d3, d3, s2[3]);
  }
  float a = (s1[0] + s1[1]) + (s1[2] + s1[3]), b = (s2[0] + s2[1]) + (s2[2] + s2[3]);
#pragma unroll
  for (int o = 16; o > 0; o >>= 1) {
    a += __shfl_xor_sync(0xffffffffu, a, o);
    b += __shfl_xor_sync(0xffffffffu, b, o);
  }
  const float md = a * (1.0f / D_MODEL);
  const float var = fmaxf(fmaf(-md, md, b * (1.0f / D_MODEL)), 0.f);
  mean_b = bf16r(k0 + md);
  float sd;
  asm("sqrt.approx.ftz.f32 %0, %1;" : "=f"(sd) : "f"(bf16r(bf16r(var) + 1e-5f)));
  asm("rcp.approx.ftz.f32 %0, %1;" : "=f"(rstd) : "f"(bf16r(sd)));
}
__device__ __forceinline__ uint32_t ln_mod2(float x0, float x1, float mean_b, float rstd, uint32_t cpair, uint32_t spair) {
  const uint32_t c1 = pack_bf16(1.0f + bf_lo(cpair), 1.0f + bf_hi(cpair));
  const uint32_t a = pack_bf16(x0 - mean_b, x1 - mean_b);
  const uint32_t n = pack_bf16(bf_lo(a) * rstd, bf_hi(a) * rstd);
  const uint32_t t = pack_bf16(bf_lo(n) * bf_lo(c1), bf_hi(n) * bf_hi(c1));
  return pack_bf16(bf_lo(t) + bf_lo(spair), bf_hi(t) + bf_hi(spair));
}

__global__ void __launch_bounds__(NTHREADS, 1)
fused_kernel(const __grid_constant__ CUtensorMap tmK, const __grid_constant__ CUtensorMap tmV,
             const __grid_constant__ CUtensorMap tmWq,
             const __grid_constant__ CUtensorMap tmWmodS,
             const __grid_constant__ CUtensorMap tmWo, const __grid_constant__ CUtensorMap tmW1,
             const __grid_constant__ CUtensorMap tmW3, const __grid_constant__ CUtensorMap tmW2,
             const Params prm) {
  extern __shared__ __align__(1024) unsigned char smem[];
  const uint32_t sb = smem_u32(smem);
  const int tid = threadIdx.x, warp = tid >> 5, lane = tid & 31;
  const int cta = blockIdx.x, G = gridDim.x;
  const uint32_t bar_full = sb + SM_BAR, bar_empty = bar_full + NS * 16, bar_post = bar_empty + NS * 8,
                 bar_tail = bar_post + NS * 8, bar_clear = bar_tail + 32, bar_mod = bar_clear + 8, bar_q = bar_mod + 8,
                 bar_wf = bar_q + 8;
  volatile uint32_t* desc = reinterpret_cast<volatile uint32_t*>(smem + SM_DESC);
  volatile uint32_t* tailslot = desc + 8;
  volatile uint32_t* s_epoch = desc + 12;
  Acc* const acc = &g_acc;
  const int h1 = cta - (G - N_H1);
  const int has_h1 = h1 >= 0 ? 1 : 0;
  const bool has_h3 = cta < N_H3;
  const int nh = has_h1 + (has_h3 ? 4 : 0);
  const bool has_f1 = cta < N_F1;
  const int f2 = G - 1 - cta;
  const bool has_f2 = cta >= N_F1 && f2 < N_F2;
  const int f2b = f2 + (G - N_F1);
  const bool has_f2b = has_f2 && f2b < N_F2;
  const int wf = cta - WF_CTA0;
  const bool has_wf = wf >= 0 && wf < 10;

  if (warp == W_PROD) {
    if (lane == 0) {
      for (int r = cta; r < D_MODEL; r += G)
        asm volatile("cp.async.bulk.prefetch.L2.global [%0], %1;" ::"l"(prm.wmod + (size_t)r * (6 * D_MODEL * 2)), "r"(2 * D_MODEL * 2) : "memory");
      mbar_init(bar_full, 1);
      mbar_init(bar_full + 8, 1);
      if (has_h1) {
        asm volatile("fence.mbarrier_init.release.cluster;" ::: "memory");
        asm volatile("fence.proxy.async.shared::cta;" ::: "memory");
        mbar_expect_tx(bar_full, 320 * 32);
        tma_3d(sb, &tmWmodS, h1 * 16, 0, 0, bar_full);
        mbar_expect_tx(bar_full + 8, 320 * 32);
        tma_3d(sb + 320 * 32, &tmWmodS, h1 * 16, 0, 5, bar_full + 8);
      }
      for (int i = 2; i < 39; i++) mbar_init(bar_full + 8 * i, 1);
      mbar_init(bar_wf, NWF - 1);
      asm volatile("fence.mbarrier_init.release.cluster;" ::: "memory");
      asm volatile("fence.proxy.async.shared::cta;" ::: "memory");
      prefetch_tm(&tmWq);
      for (int i = 0; i < nh; i++) mbar_arrive(bar_post + 8 * i);
      prefetch_tm(&tmK);
      prefetch_tm(&tmV);
      prefetch_tm(&tmWo);
    }
    __syncwarp();
    asm volatile("bar.arrive 3, 64;" ::: "memory");
    asm volatile("bar.arrive 0, %0;" ::"n"(NTHREADS - 32) : "memory");
  } else if (warp == W_JAN) {
    uint4* z = reinterpret_cast<uint4*>(acc);
    constexpr int NZ = sizeof(Acc) / 16;
    const int per = (NZ + G - 1) / G;
    for (int i = cta * per + lane; i < min(NZ, (cta + 1) * per); i += 32) z[i] = make_uint4(0, 0, 0, 0);
    __syncwarp();
    if (lane == 0) fence_gpu();
    const unsigned e = __shfl_sync(0xffffffffu, *reinterpret_cast<volatile unsigned*>(&g_epoch), 0);
    asm volatile("bar.sync 3, 64;" ::: "memory");
    if (lane == 0) mbar_arrive(bar_clear);
    uint4* nx = reinterpret_cast<uint4*>(&g_par[(e & 1) ^ 1]);
    constexpr int NZP = sizeof(Par) / 16;
    for (int i = cta * 32 + lane; i < NZP; i += G * 32) nx[i] = make_uint4(0, 0, 0, 0);
    return;
  } else if (warp == W_GATH) {
    {
      const char* pa = lane < 3 ? prm.wmod + min(lane * (2 << 20) + h1 * 32 * (h1 >= 0), 6 * D_MODEL * D_MODEL * 2 - 128)
                     : lane < 7 ? prm.wq + min((lane - 3) * (2 << 20), NH * DH * D_MODEL * 2 - 128)
                                : prm.kc + (size_t)(lane - 7) * (2 << 20) + (size_t)(cta & 63) * SLOT_BYTES;
      if (lane < 16) asm volatile("prefetch.global.L2 [%0];" ::"l"(pa));
    }
    const uint4* src = reinterpret_cast<const uint4*>(g_llmod[cta & (QRE - 1)]) + lane;
    uint4 v[10];
#pragma unroll
    for (int i = 0; i < 10; i++) v[i] = ld_relaxed_2x8(src + i * 32);
    const unsigned e = *reinterpret_cast<volatile unsigned*>(&g_epoch);
    if (lane == 0) *s_epoch = e;
    __syncwarp();
    asm volatile("bar.sync 0, %0;" ::"n"(NTHREADS - 32) : "memory");
    const unsigned tg = e + 1;
    uint32_t pend = 0x3ff, it = 0;
    for (;;) {
#pragma unroll
      for (int i = 0; i < 10; i++)
        if (((pend >> i) & 1u) && v[i].y == tg && v[i].w == tg) {
          reinterpret_cast<uint2*>(smem + SM_Q)[i * 32 + lane] = make_uint2(v[i].x, v[i].z);
          pend &= ~(1u << i);
        }
      if (!pend) break;
#pragma unroll
      for (int i = 0; i < 10; i++)
        if ((pend >> i) & 1u) v[i] = ld_relaxed_2x8(src + i * 32);
      if (++it > (1u << 22)) __trap();
    }
    __syncwarp();
    if (lane == 0) {
      mbar_arrive(bar_mod);
      const unsigned* hint = &g_par[e & 1].hintH3.v;
      uint32_t it2 = 0;
      while (ld_acquire(hint) < (unsigned)G) {
        if (++it2 > (1u << 22)) __trap();
      }
      mbar_arrive(bar_q);
    }
    return;
  } else {
    uint32_t* va = reinterpret_cast<uint32_t*>(smem + SM_VA);
    float* xs = reinterpret_cast<float*>(smem + SM_X);
    const int p1 = tid + 256;
    const uint32_t cv0 = __ldg(reinterpret_cast<const uint32_t*>(prm.c) + tid);
    const uint32_t xv0 = __ldg(reinterpret_cast<const uint32_t*>(prm.x) + tid);
    uint32_t cv1 = 0, xv1 = 0;
    if (tid < 64) {
      cv1 = __ldg(reinterpret_cast<const uint32_t*>(prm.c) + p1);
      xv1 = __ldg(reinterpret_cast<const uint32_t*>(prm.x) + p1);
    }
    va[tid] = pack_bf16(silu_f(bf_lo(cv0)), silu_f(bf_hi(cv0)));
    xs[2 * tid] = bf_lo(xv0);
    xs[2 * tid + 1] = bf_hi(xv0);
    if (tid < 64) {
      va[p1] = pack_bf16(silu_f(bf_lo(cv1)), silu_f(bf_hi(cv1)));
      xs[2 * p1] = bf_lo(xv1);
      xs[2 * p1 + 1] = bf_hi(xv1);
    }
  }
  if (warp == W_PROD) {
    if (lane != 0) return;
    uint64_t pol;
    asm volatile("createpolicy.fractional.L2::evict_first.b64 %0, 1.0;" : "=l"(pol));
    uint32_t tkA = 0, tkB = 0;
    unsigned* ticket = nullptr;
    int win = WIN_HEAD;
    bool head_phase = true;
    unsigned long long fifo = 0;
    int nfifo = 0;
    auto throttle = [&]() {
      if (nfifo >= win) {
        const uint32_t e = (uint32_t)(fifo >> (7 * (win - 1))) & 127u;
        mbar_wait(bar_full + 8 * (e >> 1), e & 1u);
      }
    };
    auto push = [&](uint32_t idx, uint32_t parity) { fifo = (fifo << 7) | (idx << 1) | parity; nfifo++; };
    uint32_t active = (1u << NS) - 1, used = 0, upar = 0;
    int cur = 0;
    auto acquire = [&]() {
      const int s = cur;
      do { cur = (cur + 1) & (NS - 1); } while (!((active >> cur) & 1u));
      if ((used >> s) & 1u) mbar_wait(bar_empty + 8 * s, ((upar >> s) & 1u) ^ 1u);
      return s;
    };
    auto post = [&](int s, uint32_t d) {
      desc[s] = d;
      mbar_arrive(bar_post + 8 * s);
    };
    auto issue_half = [&](int s, int h, const CUtensorMap* tm, int c0, int c1, uint32_t bytes, uint32_t dst) {
      throttle();
      const uint32_t bar = bar_full + 16 * s + 8 * h;
      mbar_expect_tx(bar, bytes);
      tma_2d(dst, tm, c0, c1, bar, pol);
      push(2 * s + h, (upar >> s) & 1u);
    };
    auto issue_small = [&](int s, int h, const CUtensorMap* tm, int c0, int z, uint32_t bytes) {
      throttle();
      const uint32_t bar = bar_full + 16 * s + 8 * h;
      mbar_expect_tx(bar, bytes);
      tma_3d(sb + s * SLOT_BYTES + h * bytes, tm, c0, 0, z, bar);
      push(2 * s + h, (upar >> s) & 1u);
    };
    auto done_slot = [&](int s) { upar ^= 1u << s; used |= 1u << s; };
    if (has_h1) { acquire(); push(0, 0); push(1, 0); done_slot(0); }
    for (int i = has_h1; i < nh; i++) {
      const int s = acquire();
      issue_half(s, 0, &tmWq, cta * 64, (i - has_h1) * 160, 80 * 128, sb + s * SLOT_BYTES);
      issue_half(s, 1, &tmWq, cta * 64, (i - has_h1) * 160 + 80, 80 * 128, sb + s * SLOT_BYTES + 80 * 128);
      done_slot(s);
    }
    int istat = 0;
    int wf_left = has_wf ? NWF : 0;
    bool tail_done = false, shallow = false;
    int pf_done = 0, catch_left = 0;
    for (;;) {
      uint32_t seq;
      if (istat < 0) {
        seq = NSEQ;
      } else if (istat < NSTATIC) {
        seq = cta + G * istat;
        istat++;
        if (istat == NSTATIC - 1) {
          mbar_wait(bar_mod, 0);
          ticket = &g_par[*s_epoch & 1].ticket.v;
          tkA = atomicAdd(ticket, 1u);
          tkB = atomicAdd(ticket, 1u);
        }
      } else {
        if (tkA == 0xfffffffeu) tkA = atomicAdd(ticket, 1u);
        seq = tkA == 0xffffffffu ? NSEQ : NSTATIC * G + tkA;
        tkA = tkB;
        if (seq < NSEQ) {
          if (has_wf && seq >= NSEQ - WF_LEAD) {
            tkB = 0xffffffffu;
          } else if (!shallow && seq >= NSEQ - SHALLOW_LEAD) {
            shallow = true;
            tkB = 0xfffffffeu;
          } else if (shallow) {
            tkA = atomicAdd(ticket, 1u);
          } else {
            tkB = atomicAdd(ticket, 1u);
          }
        }
      }
      if (!tail_done && seq >= NSEQ && wf_left == 0) {
        tail_done = true;
        win = WIN_FFN;
        if (has_f2) spin_ge(&acc->hintV[NH - 1].v, TPH / 2);
        const int nt = has_f1 ? 2 : has_f2b ? 4 : has_f2 ? 2 : 0;
        for (int k = 0; k < nt; k++) {
          const int ti = has_f1 ? k : (k + 2) & 3;
          const int s = acquire();
          active &= ~(1u << s);
          post(s, (uint32_t)T_END << 28);
          tailslot[ti] = s | (((upar >> s) & 1u) << 8);
          mbar_arrive(bar_tail + 8 * ti);
          if (has_f1) {
            issue_small(s, 0, ti == 0 ? &tmW1 : &tmW3, cta * 16, 0, 320 * 32);
            issue_small(s, 1, ti == 0 ? &tmW1 : &tmW3, cta * 16, 5, 320 * 32);
          } else {
            const int c0 = (ti >= 2 ? f2 : f2b) * 16, z = (ti & 1) * 6;
            issue_small(s, 0, &tmW2, c0, z, 384 * 32);
            issue_small(s, 1, &tmW2, c0, z + 3, 384 * 32);
          }
        }
      }
      int type, a, b;
      if (seq >= NSEQ) {
        if (wf_left == 0) break;
        type = T_WF; a = NH - wf_left; b = wf;
        wf_left--;
        istat = -1;
      } else if (seq >= MS_AT && seq < MS_AT + N_MSA) {
        type = T_MS; a = 0; b = N_H1 + (seq - MS_AT);
      } else if (seq >= NSEQ - (N_MS - N_MSA)) {
        type = T_MS; a = 0; b = N_H1 + N_MS - (NSEQ - seq);
      } else if (seq < NK) {
        type = T_K; a = seq >> 7; b = seq & 127;
      } else {
        uint32_t r = seq - NK - (seq >= MS_AT ? N_MSA : 0);
        if (r < LAG * TPH) {
          type = T_V; a = r >> 7; b = r & 127;
        } else {
          r -= LAG * TPH;
          constexpr uint32_t NBLK = NH - NWF;
          const uint32_t blk = r / 138u, off = r - blk * 138u;
          if (blk < NBLK) {
            if (off < TPH) { type = T_V; a = LAG + blk; b = off; }
            else { type = T_WO; a = blk; b = off - TPH; }
          } else {
            r -= NBLK * 138u;
            type = T_V; a = LAG + NBLK + (r >> 7); b = r & 127;
          }
        }
      }
      if (head_phase && ((used >> cur) & 1u)) {
        int pf = istat;
        if (pf < pf_done) pf = pf_done;
        long long t_next = clock64();
        while (pf < NSTATIC && !mbar_test(bar_empty + 8 * cur, ((upar >> cur) & 1u) ^ 1u)) {
          if (clock64() >= t_next) {
            asm volatile("cp.async.bulk.prefetch.L2.global [%0], %1;" ::"l"(prm.kc + (size_t)(cta + G * pf) * SLOT_BYTES), "r"(SLOT_BYTES) : "memory");
            pf++;
            t_next += PF_CYCLES;
          }
        }
        pf_done = pf;
      }
      const int s = acquire();
      post(s, ((uint32_t)type << 28) | (a << 16) | b);
      if (head_phase && mbar_test(bar_q, 0)) { head_phase = false; win = WIN_CATCH; catch_left = CATCH_ITEMS; }
      if (catch_left > 0 && --catch_left == 0) win = WINDOW;
      if (seq >= NSEQ - (N_MS - N_MSA) && type != T_WF) win = WIN_MS;
      const uint32_t dst = sb + s * SLOT_BYTES;
      if (type == T_MS) {
        issue_small(s, 0, &tmWmodS, b * 16, 0, 320 * 32);
        issue_small(s, 1, &tmWmodS, b * 16, 5, 320 * 32);
      } else {
        const CUtensorMap* tm = type == T_K ? &tmK : type == T_V ? &tmV : &tmWo;
        const int c0 = (type == T_K || type == T_V) ? 0 : b * 64;
        const int c1 = (type == T_K || type == T_V) ? (a * TPH + b) * 192 : a * DH;
        issue_half(s, 0, tm, c0, c1, 96 * 128, dst);
        issue_half(s, 1, tm, c0, c1 + 96, 96 * 128, dst + 96 * 128);
      }
      done_slot(s);
    }
    uint32_t pending = active;
    uint32_t it = 0;
    while (pending) {
      for (int s = 0; s < NS; s++) {
        if (!((pending >> s) & 1u)) continue;
        if (((used >> s) & 1u) && !mbar_test(bar_empty + 8 * s, ((upar >> s) & 1u) ^ 1u)) continue;
        pending &= ~(1u << s);
        post(s, (uint32_t)T_END << 28);
      }
      if (++it > (1u << 24)) __trap();
    }
    return;
  }

  asm volatile("bar.sync 0, %0;" ::"n"(NTHREADS - 32) : "memory");
  const unsigned ep = *s_epoch;
  Par* const par = &g_par[ep & 1];

  const int g = lane >> 2, j = lane & 3;
  float* xs = reinterpret_cast<float*>(smem + SM_X);
  float* red = reinterpret_cast<float*>(smem + SM_RED);
  uint32_t* vh = reinterpret_cast<uint32_t*>(smem + SM_VH);

  {
    uint32_t bf[10];
    if (has_h1) {
      uint32_t af[5][4];
      vec_frags(reinterpret_cast<const uint32_t*>(smem + SM_VA), warp, lane, bf);
      mbar_wait(bar_full + (warp >= 4 ? 8 : 0), 0);
      slice_frags(sb, warp, lane, af);
      slice_mma(af, bf, red, warp, lane);
      cons_bar();
      if (warp == 0) {
        const float v = red8(red, lane & 15);
        const float vn = __shfl_down_sync(0xffffffffu, v, 1);
        if (!(lane & 1)) {
          const uint32_t w = pack_bf16(v, vn);
          st_relaxed_v2(&g_llmod[(lane >> 4) * 2][h1 * 8 + ((lane & 15) >> 1)], w, ep + 1);
          st_relaxed_v2(&g_llmod[(lane >> 4) * 2 + 1][h1 * 8 + ((lane & 15) >> 1)], w, ep + 1);
        }
        if (lane == 0) mbar_arrive(bar_empty);
        __syncwarp();
      }
    }
    float mean_b, rstd;
    ln_stats(xs, lane, mean_b, rstd);
    const uint32_t* sc = reinterpret_cast<const uint32_t*>(smem + SM_Q);
    mbar_wait(bar_mod, 0);
    for (int p = tid; p < D_MODEL / 2; p += 256) vh[p] = ln_mod2(xs[2 * p], xs[2 * p + 1], mean_b, rstd, sc[320 + p], sc[p]);
    __syncwarp();
    cons_bar();
    if (has_h3) {
      vec_frags(vh, warp, lane, bf);
      const int sl = has_h1 + (warp >> 1);
      mbar_wait(bar_full + 16 * sl + 8 * (warp & 1), 0);
      const int r0 = (lane & 7) + ((lane >> 4) << 3), lo = (lane >> 3) & 1;
      const uint32_t vg = sb + sl * SLOT_BYTES + ((warp & 1) * 80 + r0) * 128 + ((lo ^ (r0 & 7)) << 4);
      float qa[4][4];
#pragma unroll
      for (int m = 0; m < 4; m++) { qa[m][0] = qa[m][1] = qa[m][2] = qa[m][3] = 0.f; }
#pragma unroll
      for (int ks = 0; ks < 5; ks++) {
#pragma unroll
        for (int m = 0; m < 4; m++) {
          uint32_t a4[4];
          ldsm4t(a4, (vg + ks * 2048) ^ (m << 5));
          mma16816(qa[m], a4, bf[2 * ks], bf[2 * ks + 1]);
        }
      }
      red[(16 * j + g) * 8 + warp] = sel4(j, qa[0][0], qa[1][0], qa[2][0], qa[3][0]);
      red[(16 * j + 8 + g) * 8 + warp] = sel4(j, qa[0][2], qa[1][2], qa[2][2], qa[3][2]);
      cons_bar();
      if (tid < 64) {
        mbar_wait(bar_clear, 0);
        const float v = red8(red, tid);
        const float vn = __shfl_down_sync(0xffffffffu, v, 1);
        if (!(tid & 1)) {
          const uint32_t w = ~pack_bf16(v, vn);
#pragma unroll
          for (int r = 0; r < QRE; r++) st_relaxed(&par->llq[r][cta * 32 + (tid >> 1)], w);
        }
        if (tid < 4) mbar_arrive(bar_empty + 8 * (has_h1 + tid));
        __syncwarp();
        if (tid == 32) red_add_u32(&par->hintH3.v, 1u);
      }
    } else if (tid == 0) {
      mbar_wait(bar_clear, 0);
      red_add_u32(&par->hintH3.v, 1u);
    }
    mbar_wait(bar_q, 0);
    {
      uint32_t pend = 7, it = 0;
      while (pend) {
        uint4 v[3];
#pragma unroll
        for (int i = 0; i < 3; i++)
          if ((pend >> i) & 1u) v[i] = ld_relaxed_v4(reinterpret_cast<const uint4*>(par->llq[cta & (QRE - 1)]) + i * 256 + tid);
#pragma unroll
        for (int i = 0; i < 3; i++)
          if (((pend >> i) & 1u) && v[i].x != 0u && v[i].y != 0u && v[i].z != 0u && v[i].w != 0u) {
            reinterpret_cast<uint4*>(smem + SM_Q)[i * 256 + tid] = make_uint4(~v[i].x, ~v[i].y, ~v[i].z, ~v[i].w);
            pend &= ~(1u << i);
          }
        if (++it > (1u << 22)) __trap();
      }
    }
    __syncwarp();
    cons_bar();
    if (tid == 0 && cta == 0) g_epoch = ep + 1;
  }

  {
    const uint32_t slot = sb + warp * SLOT_BYTES;
    const uint32_t my_full = bar_full + 16 * warp, my_empty = bar_empty + 8 * warp, my_post = bar_post + 8 * warp;
    uint32_t* stage = reinterpret_cast<uint32_t*>(smem + SM_STAGE + warp * 768);
    uint32_t vk[3], vv[3];
    {
      const int r0 = (lane & 7) + (((lane >> 3) & 1) << 3), hi = lane >> 4;
      const int r1 = (lane & 7) + ((lane >> 4) << 3), lo = (lane >> 3) & 1;
#pragma unroll
      for (int t = 0; t < 3; t++) {
        vk[t] = slot + (3 * r0 + t) * 128 + ((hi ^ ((3 * r0 + t) & 7)) << 4);
        vv[t] = slot + (3 * r1 + t) * 128 + ((lo ^ ((3 * r1 + t) & 7)) << 4);
      }
    }
    uint32_t use = (warp < nh) ? 1 : 0;
    for (;; use++) {
      mbar_wait(my_post, use & 1);
      const uint32_t d = desc[warp];
      const int type = d >> 28, a = (d >> 16) & 0xfff, b = d & 0xffff;
      if (type == T_K) {
        const uint32_t* q32 = reinterpret_cast<const uint32_t*>(smem + SM_Q) + a * (DH / 2);
        float s[4][4];
#pragma unroll
        for (int m = 0; m < 4; m++) { s[m][0] = s[m][1] = s[m][2] = s[m][3] = 0.f; }
        mbar_wait(my_full, use & 1);
        mbar_wait(my_full + 8, use & 1);
#pragma unroll
        for (int ks = 0; ks < 12; ks++) {
          const uint32_t b0 = q32[8 * ks + j], b1 = q32[8 * ks + 4 + j];
#pragma unroll
          for (int m = 0; m < 4; m++) {
            uint32_t af[4];
            ldsm4(af, (vk[ks >> 2] ^ ((ks & 3) << 5)) + m * 6144);
            mma16816(s[m], af, b0, b1);
          }
        }
        __syncwarp();
        if (lane == 0) mbar_arrive(my_empty);
        const float scale = 0.07216878364870323f;
        const float s0 = bf16r(sel4(j, s[0][0], s[1][0], s[2][0], s[3][0])) * scale;
        const float s1 = bf16r(sel4(j, s[0][2], s[1][2], s[2][2], s[3][2])) * scale;
        __nv_bfloat16* st16 = reinterpret_cast<__nv_bfloat16*>(stage);
        st16[16 * j + g] = __float2bfloat16_rn(s0);
        st16[16 * j + 8 + g] = __float2bfloat16_rn(s1);
        __syncwarp();
        const uint32_t pr = stage[lane];
        st_relaxed_v2(&g_sc[a * (SK / 2) + b * 32 + lane], pr, ep + 1);
        const float e0 = bf_lo(pr), e1 = bf_hi(pr);
        const float tmax = warp_max(fmaxf(e0, e1));
        const float tsum = warp_sum(fast_exp(e0 - tmax) + fast_exp(e1 - tmax));
        unsigned old = 0;
        if (lane == 0) {
          st_relaxed_f2(&acc->tstat[a * TPH + b], tmax, tsum);
          old = atomicAdd(&acc->cntK[a].v, 1u);
        }
        old = __shfl_sync(0xffffffffu, old, 0);
        if (old == TPH - 1) {
          float4 t0, t1;
          uint32_t it = 0;
          do {
            const uint4 r0 = ld_relaxed_2x8(acc->tstat + a * TPH + 2 * lane), r1 = ld_relaxed_2x8(acc->tstat + a * TPH + 64 + 2 * lane);
            t0 = make_float4(__uint_as_float(r0.x), __uint_as_float(r0.y), __uint_as_float(r0.z), __uint_as_float(r0.w));
            t1 = make_float4(__uint_as_float(r1.x), __uint_as_float(r1.y), __uint_as_float(r1.z), __uint_as_float(r1.w));
            if (++it > (1u << 22)) __trap();
          } while (t0.y == 0.f || t0.w == 0.f || t1.y == 0.f || t1.w == 0.f);
          __syncwarp();
          const float m = warp_max(fmaxf(fmaxf(t0.x, t0.z), fmaxf(t1.x, t1.z)));
          const float l = warp_sum(t0.y * fast_exp(t0.x - m) + t0.w * fast_exp(t0.z - m) +
                                   t1.y * fast_exp(t1.x - m) + t1.w * fast_exp(t1.z - m));
          if (lane == 0) st_relaxed_f2(&acc->hstat[a], m, 1.0f / l);
        }
      } else if (type == T_V) {
        {
          float2 hs;
          uint2 sv;
          uint32_t it = 0;
          do {
            hs = ld_relaxed_f2(reinterpret_cast<const float*>(&acc->hstat[a]));
            sv = ld_relaxed_v2(&g_sc[a * (SK / 2) + b * 32 + lane]);
            if (++it > (1u << 22)) __trap();
          } while (hs.y == 0.f || sv.y != ep + 1);
          const uint32_t pr = sv.x;
          stage[lane] = pack_bf16(fast_exp(bf_lo(pr) - hs.x) * hs.y, fast_exp(bf_hi(pr) - hs.x) * hs.y);
        }
        __syncwarp();
        uint32_t pb[8];
#pragma unroll
        for (int i = 0; i < 8; i++) pb[i] = stage[4 * i + j];
        float o[12][4];
#pragma unroll
        for (int m = 0; m < 12; m++) { o[m][0] = o[m][1] = o[m][2] = o[m][3] = 0.f; }
        mbar_wait(my_full, use & 1);
        mbar_wait(my_full + 8, use & 1);
#pragma unroll
        for (int ks = 0; ks < 4; ks++) {
#pragma unroll
          for (int m = 0; m < 12; m++) {
            uint32_t af[4];
            ldsm4t(af, (vv[m >> 2] ^ ((m & 3) << 5)) + ks * 6144);
            mma16816(o[m], af, pb[2 * ks], pb[2 * ks + 1]);
          }
        }
        __syncwarp();
        if (lane == 0) mbar_arrive(my_empty);
        {
          float* sf = reinterpret_cast<float*>(stage);
#pragma unroll
          for (int i = 0; i < 3; i++) {
            sf[16 * (4 * i + j) + g] = sel4(j, o[4 * i][0], o[4 * i + 1][0], o[4 * i + 2][0], o[4 * i + 3][0]);
            sf[16 * (4 * i + j) + 8 + g] = sel4(j, o[4 * i][2], o[4 * i + 1][2], o[4 * i + 2][2], o[4 * i + 3][2]);
          }
          __syncwarp();
          float4* dst = acc->o[a][cta & (ORE - 1)];
          red_add_v4(dst + lane, sf[3 * lane], sf[3 * lane + 1], sf[3 * lane + 2], 1.0f);
          red_add_v4(dst + 32 + lane, sf[96 + 3 * lane], sf[96 + 3 * lane + 1], sf[96 + 3 * lane + 2], 1.0f);
          __syncwarp();
          if (lane == 0) red_add_u32(&acc->hintV[a].v, 1u);
        }
      } else if (type == T_WO || type == T_WF) {
        const int c0 = b * 64 + 16 * j + g;
        const bool last = type == T_WF && a == NH - 1;
        float pre0 = 0.f, pre1 = 0.f;
        uint2 gw0 = make_uint2(0u, 0u), gw1 = make_uint2(0u, 0u);
        if (last) {
          const uint2* gp = &g_llmod[cta & (QRE - 1)][2 * (D_MODEL / 2)];
          uint32_t itg = 0;
          do {
            gw0 = ld_relaxed_v2(gp + (c0 >> 1)); gw1 = ld_relaxed_v2(gp + ((c0 + 8) >> 1));
            if (++itg > (1u << 22)) __trap();
          } while (gw0.y != ep + 1 || gw1.y != ep + 1);
          __syncwarp();
          {
            float2 t0, t1;
            uint32_t it = 0;
            do {
              t0 = ld_relaxed_f2(reinterpret_cast<const float*>(acc->attn + c0));
              t1 = ld_relaxed_f2(reinterpret_cast<const float*>(acc->attn + c0 + 8));
              if (++it > (1u << 22)) __trap();
            } while (t0.y != (float)(NH - NWF) || t1.y != (float)(NH - NWF));
            pre0 = t0.x; pre1 = t1.x;
          }
          __syncwarp();
        }
        {
          float4 u0, u1;
          uint32_t it = 0;
          if (lane == 0) spin_ge(&acc->hintV[a].v, type == T_WF ? TPH / 2 : TPH);
          __syncwarp();
          for (;;) {
            float4 t[2][ORE];
#pragma unroll
            for (int r = 0; r < ORE; r++) { t[0][r] = ld_relaxed_f4(&acc->o[a][r][lane]); t[1][r] = ld_relaxed_f4(&acc->o[a][r][32 + lane]); }
            u0 = t[0][0]; u1 = t[1][0];
#pragma unroll
            for (int r = 1; r < ORE; r++) {
              u0.x += t[0][r].x; u0.y += t[0][r].y; u0.z += t[0][r].z; u0.w += t[0][r].w;
              u1.x += t[1][r].x; u1.y += t[1][r].y; u1.z += t[1][r].z; u1.w += t[1][r].w;
            }
            if (__all_sync(0xffffffffu, u0.w == (float)TPH && u1.w == (float)TPH)) break;
            if (++it > (1u << 22)) __trap();
          }
          __nv_bfloat16* s16 = reinterpret_cast<__nv_bfloat16*>(stage);
          s16[3 * lane] = __float2bfloat16_rn(u0.x); s16[3 * lane + 1] = __float2bfloat16_rn(u0.y); s16[3 * lane + 2] = __float2bfloat16_rn(u0.z);
          s16[96 + 3 * lane] = __float2bfloat16_rn(u1.x); s16[96 + 3 * lane + 1] = __float2bfloat16_rn(u1.y); s16[96 + 3 * lane + 2] = __float2bfloat16_rn(u1.z);
        }
        __syncwarp();
        mbar_wait(my_full, use & 1);
        mbar_wait(my_full + 8, use & 1);
        float v0, v1;
        gemv_tile<12>(slot, stage, lane, v0, v1);
        __syncwarp();
        if (lane == 0) mbar_arrive(my_empty);
        if (type == T_WO) {
          red_add_v2(acc->attn + c0, v0, 1.0f);
          red_add_v2(acc->attn + c0 + 8, v1, 1.0f);
        } else if (!last) {
          red[(NH - 1 - a) * 64 + 16 * j + g] = v0; red[(NH - 1 - a) * 64 + 16 * j + 8 + g] = v1;
          __syncwarp();
          if (lane == 0) mbar_arrive(bar_wf);
        } else {
          const float ga0 = (g & 1) ? bf_hi(gw0.x) : bf_lo(gw0.x), ga1 = (g & 1) ? bf_hi(gw1.x) : bf_lo(gw1.x);
          mbar_wait(bar_wf, 0);
#pragma unroll
          for (int w = 1; w < NWF; w++) { pre0 += red[w * 64 + 16 * j + g]; pre1 += red[w * 64 + 16 * j + 8 + g]; }
          const float x0 = bf16r(xs[c0] + bf16r(ga0 * bf16r(pre0 + v0)));
          const float x1 = bf16r(xs[c0 + 8] + bf16r(ga1 * bf16r(pre1 + v1)));
          const float n0 = __shfl_down_sync(0xffffffffu, x0, 4), n1 = __shfl_down_sync(0xffffffffu, x1, 4);
          if (!(g & 1)) {
            const uint32_t w0 = ~pack_bf16(x0, n0), w1 = ~pack_bf16(x1, n1);
#pragma unroll
            for (int r = 0; r < XRE; r++) {
              st_relaxed(&acc->llx1[r][c0 >> 1], w0);
              st_relaxed(&acc->llx1[r][(c0 + 8) >> 1], w1);
            }
          }
        }
      } else if (type == T_MS) {
        const uint32_t* va32 = reinterpret_cast<const uint32_t*>(smem + SM_VA);
        const int r0 = (lane & 7) + ((lane >> 4) << 3), lo = (lane >> 3) & 1;
        const uint32_t w = slot + r0 * 32 + ((lo ^ ((r0 >> 2) & 1)) << 4);
        float ma[4][4];
#pragma unroll
        for (int i = 0; i < 4; i++) { ma[i][0] = ma[i][1] = ma[i][2] = ma[i][3] = 0.f; }
        mbar_wait(my_full, use & 1);
        mbar_wait(my_full + 8, use & 1);
#pragma unroll 2
        for (int k4 = 0; k4 < 10; k4++) {
#pragma unroll
          for (int i = 0; i < 4; i++) {
            uint32_t af[4];
            ldsm4t(af, w + (4 * k4 + i) * 512);
            mma16816(ma[i], af, va32[8 * (4 * k4 + i) + j], va32[8 * (4 * k4 + i) + 4 + j]);
          }
        }
        __syncwarp();
        if (lane == 0) mbar_arrive(my_empty);
        const float v0 = (ma[0][0] + ma[1][0]) + (ma[2][0] + ma[3][0]), v1 = (ma[0][2] + ma[1][2]) + (ma[2][2] + ma[3][2]);
        const float n0 = __shfl_down_sync(0xffffffffu, v0, 4), n1 = __shfl_down_sync(0xffffffffu, v1, 4);
        if (!(g & 1)) {
          st_relaxed_v2(&g_llmod[j][b * 8 + (g >> 1)], pack_bf16(v0, n0), ep + 1);
          st_relaxed_v2(&g_llmod[j][b * 8 + 4 + (g >> 1)], pack_bf16(v1, n1), ep + 1);
        }
      } else {
        break;
      }
    }
  }

  uint32_t f1a[5][4], f1b[5][4], f2a[12][4];
  uint32_t sbp[4] = {0u, 0u, 0u, 0u}, cbp[4] = {0u, 0u, 0u, 0u};
  float gb = 0.f;
  const int gt = tid < 80 ? tid : tid - 16;
  const uint2* modp = g_llmod[cta & (QRE - 1)];
  auto mod_word = [&](int w) {
    uint2 v;
    uint32_t it = 0;
    do {
      v = ld_relaxed_v2(modp + w);
      if (++it > (1u << 22)) __trap();
    } while (v.y != ep + 1);
    return v.x;
  };
  auto tail_wait = [&](int ti, int h) {
    mbar_wait(bar_tail + 8 * ti, 0);
    const uint32_t ts = tailslot[ti];
    mbar_wait(bar_full + 16 * (ts & 7u) + 8 * h, ts >> 8);
    return sb + (ts & 7u) * SLOT_BYTES;
  };
  if (has_f1) {
    if (tid < 96) {
      uint32_t it = 0;
      uint4 s0, s1, c0, c1;
      const unsigned tg = ep + 1;
      do {
        s0 = ld_relaxed_2x8(modp + 3 * 320 + 4 * gt); s1 = ld_relaxed_2x8(modp + 3 * 320 + 4 * gt + 2);
        c0 = ld_relaxed_2x8(modp + 4 * 320 + 4 * gt); c1 = ld_relaxed_2x8(modp + 4 * 320 + 4 * gt + 2);
        if (++it > (1u << 22)) __trap();
      } while (s0.y != tg || s0.w != tg || s1.y != tg || s1.w != tg || c0.y != tg || c0.w != tg || c1.y != tg || c1.w != tg);
      sbp[0] = s0.x; sbp[1] = s0.z; sbp[2] = s1.x; sbp[3] = s1.z;
      cbp[0] = pack_bf16(1.0f + bf_lo(c0.x), 1.0f + bf_hi(c0.x)); cbp[1] = pack_bf16(1.0f + bf_lo(c0.z), 1.0f + bf_hi(c0.z));
      cbp[2] = pack_bf16(1.0f + bf_lo(c1.x), 1.0f + bf_hi(c1.x)); cbp[3] = pack_bf16(1.0f + bf_lo(c1.z), 1.0f + bf_hi(c1.z));
    }
    __syncwarp();
    slice_frags(tail_wait(0, warp >= 4), warp, lane, f1a);
    slice_frags(tail_wait(1, warp >= 4), warp, lane, f1b);
  }
  auto f2_preload = [&]() {
    if (tid < (has_f2b ? 32 : 16)) {
      const uint32_t w = mod_word(5 * 320 + (tid < 16 ? f2 : f2b) * 8 + ((tid & 15) >> 1));
      gb = (tid & 1) ? bf_hi(w) : bf_lo(w);
    }
    __syncwarp();
    const int r0 = (lane & 7) + ((lane >> 4) << 3), lo = (lane >> 3) & 1;
    const uint32_t base = tail_wait(2 + (warp >> 2), (warp >> 1) & 1) + ((warp & 3) * 192 + r0) * 32 + ((lo ^ ((r0 >> 2) & 1)) << 4);
#pragma unroll
    for (int ks = 0; ks < 12; ks++) ldsm4t(f2a[ks], base + ks * 512);
  };
  if (has_f2) f2_preload();
  if (tid < 96) {
    uint4 v;
    uint32_t it = 0;
    do {
      v = ld_relaxed_v4(reinterpret_cast<const uint4*>(acc->llx1[cta & (XRE - 1)]) + gt);
      if (++it > (1u << 22)) __trap();
    } while (v.x == 0u || v.y == 0u || v.z == 0u || v.w == 0u);
    __syncwarp();
    float x[8] = {bf_lo(~v.x), bf_hi(~v.x), bf_lo(~v.y), bf_hi(~v.y), bf_lo(~v.z), bf_hi(~v.z), bf_lo(~v.w), bf_hi(~v.w)};
    if (has_f2) {
      float4* xd = reinterpret_cast<float4*>(xs) + 2 * gt;
      xd[0] = make_float4(x[0], x[1], x[2], x[3]);
      xd[1] = make_float4(x[4], x[5], x[6], x[7]);
    }
    if (has_f1) {
      float m = (((x[0] + x[1]) + (x[2] + x[3])) + ((x[4] + x[5]) + (x[6] + x[7]))) * 0.125f;
      float q = 0.f, q2 = 0.f;
#pragma unroll
      for (int e = 0; e < 4; e++) {
        const float d0 = x[e] - m, d1 = x[4 + e] - m;
        q = fmaf(d0, d0, q); q2 = fmaf(d1, d1, q2);
      }
      q += q2;
#pragma unroll
      for (int o = 0; o < 5; o++) {
        const float mo = __shfl_xor_sync(0xffffffffu, m, 1 << o), qo = __shfl_xor_sync(0xffffffffu, q, 1 << o);
        const float d = mo - m;
        m = 0.5f * (m + mo);
        q = fmaf(d * d, (float)(4 << o), q + qo);
      }
      float* stat = red + 384;
      if (lane == 0) { stat[2 * warp] = m; stat[2 * warp + 1] = q; }
      asm volatile("bar.sync 4, 96;" ::: "memory");
      const float m0 = stat[0], q0 = stat[1], m1 = stat[2], q1 = stat[3], m2 = stat[4], qd = stat[5];
      const float mean = (0.4f * (m0 + m1)) + 0.2f * m2;
      const float e0 = m0 - mean, e1 = m1 - mean, e2 = m2 - mean;
      const float var = (q0 + q1 + 0.5f * qd + 256.f * (e0 * e0 + e1 * e1) + 128.f * e2 * e2) * (1.0f / D_MODEL);
      const float mean_b = bf16r(mean);
      float sd, rstd;
      asm("sqrt.approx.ftz.f32 %0, %1;" : "=f"(sd) : "f"(bf16r(bf16r(var) + 1e-5f)));
      asm("rcp.approx.ftz.f32 %0, %1;" : "=f"(rstd) : "f"(bf16r(sd)));
      uint32_t h[4];
#pragma unroll
      for (int e = 0; e < 4; e++) {
        const uint32_t a = pack_bf16(x[2 * e] - mean_b, x[2 * e + 1] - mean_b);
        const uint32_t nn = pack_bf16(bf_lo(a) * rstd, bf_hi(a) * rstd);
        const uint32_t t = pack_bf16(bf_lo(nn) * bf_lo(cbp[e]), bf_hi(nn) * bf_hi(cbp[e]));
        h[e] = pack_bf16(bf_lo(t) + bf_lo(sbp[e]), bf_hi(t) + bf_hi(sbp[e]));
      }
      reinterpret_cast<uint4*>(vh)[gt] = make_uint4(h[0], h[1], h[2], h[3]);
    }
    __syncwarp();
  }
  cons_bar();
  if (has_f1) {
    uint32_t bf[10];
    vec_frags(vh, warp, lane, bf);
    slice_mma(f1a, bf, red, warp, lane);
    slice_mma(f1b, bf, red + 128, warp, lane);
    cons_bar();
    if (warp == 0) {
      const float v = bf16r(red8(red, lane));
      const float up = __shfl_down_sync(0xffffffffu, v, 16);
      const float hh = bf16r(bf16r(silu_f(v)) * up);
      const float hn = __shfl_down_sync(0xffffffffu, hh, 1);
      const uint32_t hw = ~pack_bf16(hh, hn);
      const int wi = lane >> 1;
      if (lane < 16 && !(lane & 1)) st_relaxed(&acc->llhh[16 * (cta >> 1) + 4 * (wi & 3) + 2 * (cta & 1) + (wi >> 2)], hw);
      __syncwarp();
    }
  }
  if (has_f2) {
    uint4 hv[6];
    {
      uint32_t pend = 0x3f, it = 0;
#pragma unroll
      for (int t = 0; t < 6; t++) hv[t] = make_uint4(0u, 0u, 0u, 0u);
      const uint4* src = reinterpret_cast<const uint4*>(acc->llhh) + 24 * warp + j;
      while (pend) {
#pragma unroll
        for (int t = 0; t < 6; t++)
          if ((pend >> t) & 1u) hv[t] = ld_relaxed_v4(src + 4 * t);
#pragma unroll
        for (int t = 0; t < 6; t++)
          if (hv[t].x != 0u && hv[t].y != 0u && hv[t].z != 0u && hv[t].w != 0u) pend &= ~(1u << t);
        if (++it > (1u << 22)) __trap();
      }
      __syncwarp();
    }
    float oa[4][4];
#pragma unroll
    for (int i = 0; i < 4; i++) { oa[i][0] = oa[i][1] = oa[i][2] = oa[i][3] = 0.f; }
#pragma unroll
    for (int t = 0; t < 6; t++) {
      mma16816(oa[(2 * t) & 3], f2a[2 * t], ~hv[t].x, ~hv[t].y);
      mma16816(oa[(2 * t + 1) & 3], f2a[2 * t + 1], ~hv[t].z, ~hv[t].w);
    }
    float* red2 = red + 256;
    if (j == 0) {
      red2[g * 8 + warp] = (oa[0][0] + oa[1][0]) + (oa[2][0] + oa[3][0]);
      red2[(8 + g) * 8 + warp] = (oa[0][2] + oa[1][2]) + (oa[2][2] + oa[3][2]);
    }
    if (has_f2b) {
      const int r0 = (lane & 7) + ((lane >> 4) << 3), lo = (lane >> 3) & 1;
      const uint32_t base = tail_wait(warp >> 2, (warp >> 1) & 1) + ((warp & 3) * 192 + r0) * 32 + ((lo ^ ((r0 >> 2) & 1)) << 4);
#pragma unroll
      for (int i = 0; i < 4; i++) { oa[i][0] = oa[i][1] = oa[i][2] = oa[i][3] = 0.f; }
#pragma unroll
      for (int t = 0; t < 6; t++) {
        uint32_t a0[4], a1[4];
        ldsm4t(a0, base + (2 * t) * 512);
        ldsm4t(a1, base + (2 * t + 1) * 512);
        mma16816(oa[(2 * t) & 3], a0, ~hv[t].x, ~hv[t].y);
        mma16816(oa[(2 * t + 1) & 3], a1, ~hv[t].z, ~hv[t].w);
      }
      if (j == 0) {
        red2[(16 + g) * 8 + warp] = (oa[0][0] + oa[1][0]) + (oa[2][0] + oa[3][0]);
        red2[(24 + g) * 8 + warp] = (oa[0][2] + oa[1][2]) + (oa[2][2] + oa[3][2]);
      }
    }
    cons_bar();
    if (tid < (has_f2b ? 32 : 16)) {
      const int col = (tid < 16 ? f2 : f2b) * 16 + (tid & 15);
      prm.out[col] = __float2bfloat16_rn(xs[col] + bf16r(gb * bf16r(red8(red2, tid))));
    }
  }
}

typedef CUresult (*EncodeFn)(CUtensorMap*, CUtensorMapDataType, cuuint32_t, void*, const cuuint64_t*,
                             const cuuint64_t*, const cuuint32_t*, const cuuint32_t*, CUtensorMapInterleave,
                             CUtensorMapSwizzle, CUtensorMapL2promotion, CUtensorMapFloatOOBfill);

void make_map(EncodeFn fn, CUtensorMap* tm, const void* base, int rank, const cuuint64_t* dims,
              const cuuint64_t* strides, const cuuint32_t* box, CUtensorMapSwizzle sw, CUtensorMapL2promotion pr) {
  cuuint32_t es[3] = {1, 1, 1};
  fn(tm, CU_TENSOR_MAP_DATA_TYPE_BFLOAT16, rank, const_cast<void*>(base), dims, strides, box, es,
     CU_TENSOR_MAP_INTERLEAVE_NONE, sw, pr, CU_TENSOR_MAP_FLOAT_OOB_FILL_NONE);
}

}

extern "C" void kernel_launch(void* const* d_in, const int* in_sizes, int n_in, void* d_out, int out_size) {
  (void)in_sizes; (void)n_in; (void)out_size;
  static EncodeFn encode = nullptr;
  static int num_sms = 0;
  if (!encode) {
    void* fn = nullptr;
    cudaDriverEntryPointQueryResult qr;
    cudaGetDriverEntryPoint("cuTensorMapEncodeTiled", &fn, cudaEnableDefault, &qr);
    encode = reinterpret_cast<EncodeFn>(fn);
    int dev = 0;
    cudaGetDevice(&dev);
    cudaDeviceGetAttribute(&num_sms, cudaDevAttrMultiProcessorCount, dev);
    if (num_sms > MAX_CTAS) num_sms = MAX_CTAS;
    cudaFuncSetAttribute(fused_kernel, cudaFuncAttributeMaxDynamicSharedMemorySize, SM_TOTAL);
  }
  if (num_sms < MIN_CTAS) return;
  CUtensorMap tmK, tmV, tmWq, tmWmodS, tmWo, tmW1, tmW3, tmW2;
  const CUtensorMapL2promotion P128 = CU_TENSOR_MAP_L2_PROMOTION_L2_128B, P0 = CU_TENSOR_MAP_L2_PROMOTION_NONE;
  {
    cuuint64_t dims[2] = {64, (cuuint64_t)NH * SK * 3}, str[1] = {128};
    cuuint32_t box[2] = {64, 96};
    make_map(encode, &tmK, d_in[1], 2, dims, str, box, CU_TENSOR_MAP_SWIZZLE_128B, P0);
    make_map(encode, &tmV, d_in[2], 2, dims, str, box, CU_TENSOR_MAP_SWIZZLE_128B, P0);
  }
  {
    cuuint64_t dims[2] = {NH * DH, D_MODEL}, str[1] = {NH * DH * 2};
    cuuint32_t box[2] = {64, 80};
    make_map(encode, &tmWq, d_in[3], 2, dims, str, box, CU_TENSOR_MAP_SWIZZLE_128B, P128);
  }
  {
    cuuint64_t dims3[3] = {6 * D_MODEL, 64, 10}, str3[2] = {6 * D_MODEL * 2, 64 * 6 * D_MODEL * 2};
    cuuint32_t box3[3] = {16, 64, 5};
    make_map(encode, &tmWmodS, d_in[10], 3, dims3, str3, box3, CU_TENSOR_MAP_SWIZZLE_32B, P128);
  }
  {
    cuuint64_t dims[2] = {D_MODEL, NH * DH}, str[1] = {D_MODEL * 2};
    cuuint32_t box[2] = {64, 96};
    make_map(encode, &tmWo, d_in[4], 2, dims, str, box, CU_TENSOR_MAP_SWIZZLE_128B, P128);
  }
  {
    cuuint64_t dims[3] = {FF, 64, 10}, str[2] = {FF * 2, 64 * FF * 2};
    cuuint32_t box[3] = {16, 64, 5};
    make_map(encode, &tmW1, d_in[6], 3, dims, str, box, CU_TENSOR_MAP_SWIZZLE_32B, P128);
    make_map(encode, &tmW3, d_in[7], 3, dims, str, box, CU_TENSOR_MAP_SWIZZLE_32B, P128);
  }
  {
    cuuint64_t dims[3] = {D_MODEL, 128, 12}, str[2] = {D_MODEL * 2, 128 * D_MODEL * 2};
    cuuint32_t box[3] = {16, 128, 3};
    make_map(encode, &tmW2, d_in[8], 3, dims, str, box, CU_TENSOR_MAP_SWIZZLE_32B, P128);
  }
  Params prm;
  prm.x = (const __nv_bfloat16*)d_in[0];
  prm.c = (const __nv_bfloat16*)d_in[9];
  prm.wmod = (const char*)d_in[10];
  prm.wq = (const char*)d_in[3];
  prm.kc = (const char*)d_in[1];
  prm.out = (__nv_bfloat16*)d_out;
  fused_kernel<<<num_sms, NTHREADS, SM_TOTAL, cudaStreamPerThread>>>(tmK, tmV, tmWq, tmWmodS, tmWo, tmW1, tmW3, tmW2, prm);
}
```
